```python
import torch

def _softmax(x, axis=-1):
    return torch.softmax(x, dim=axis)
def _gelu(x):
    return torch.nn.functional.gelu(x, approximate="tanh")
def _silu(x):
    return torch.nn.functional.silu(x)
def _sigmoid(x):
    return torch.sigmoid(x)
def _layernorm(x, axis=-1, eps=1e-5):
    m = x.mean(dim=axis, keepdim=True)
    v = x.var(dim=axis, keepdim=True, unbiased=False)
    return (x - m) / torch.sqrt(v + eps)
def _scatter_add(tgt, idx, src, axis=0):
    return tgt.clone().index_add_(axis, idx, src)
def _segment_sum(src, seg, n):
    out = torch.zeros((n,) + src.shape[1:], dtype=src.dtype)
    return out.index_add_(0, seg, src)
def _pad(x, pw):
    flat = tuple(v for pair in reversed(pw) for v in pair)
    return torch.nn.functional.pad(x, flat)

kernel_name = 'sequential_preLN__sliding_block_cached__dense_activation_silu__decode'

def setup_inputs():

    _w = (lambda a: (lambda t: t.to(torch.bfloat16) if t.is_floating_point() else t)(torch.as_tensor(a)))
    def _A_setup():
        B, Sq, D = 1, 1, 576
        Hq, Hkv, Sk, Dh = 32, 16, 8192, 128
        assert Hq % Hkv == 0, (Hq, Hkv)
        return {
            "x": _w((lambda *s: torch.randn(*s, dtype=torch.bfloat16) * 0.05)(B, Sq, D)),
            "k_cache": _w((lambda *s: torch.randn(*s, dtype=torch.bfloat16) * 3.2)(B, Hkv, Sk, Dh)),
            "v_cache": _w((lambda *s: torch.randn(*s, dtype=torch.bfloat16) * 0.8)(B, Hkv, Sk, Dh)),
            "wq": _w((lambda *s: torch.randn(*s, dtype=torch.bfloat16) * 3.2)(D, Hq * Dh) * (D ** -0.5)),
            "wo": _w((lambda *s: torch.randn(*s, dtype=torch.bfloat16) * 0.8)(Hq * Dh, D) * ((Hq * Dh) ** -0.5)),
        }
    _A_in = _A_setup()

    def _B_setup():
        B, S, D, F = 1, 1, 576, 4608
        return {
            "x": _w((lambda *s: torch.randn(*s, dtype=torch.bfloat16) * 0.05)(B, S, D)),
            "w1": _w((lambda *s: torch.randn(*s, dtype=torch.bfloat16) * 3.2)(D, F) * (D ** -0.5)),
            "w2": _w((lambda *s: torch.randn(*s, dtype=torch.bfloat16) * 0.4)(F, D) * (F ** -0.5)),
        }
    _B_in = _B_setup()

    return {
        "A_x": _A_in["x"],
        "A_k_cache": _A_in["k_cache"],
        "A_v_cache": _A_in["v_cache"],
        "A_wq": _A_in["wq"],
        "A_wo": _A_in["wo"],
        "B_x": _B_in["x"],
        "B_w1": _B_in["w1"],
        "B_w2": _B_in["w2"],
    }

def reference(A_x, A_k_cache, A_v_cache, A_wq, A_wo, B_x, B_w1, B_w2):
    def _A_ref(x, k_cache, v_cache, wq, wo):
        B, Sq, D = x.shape
        Hq, Dh = 32, 128
        Hkv, Sk = k_cache.shape[1], k_cache.shape[2]
        W = min(4096, max(256, Sk // 4))
        rep = Hq // Hkv
        q = (lambda x, *d: x.permute(*d))((x @ wq).reshape(B, Sq, Hq, Dh), 0, 2, 1, 3)
        k = (lambda x, n, axis: torch.repeat_interleave(x, n, dim=axis))(k_cache[:, :, Sk - W:, :], rep, axis=1)
        v = (lambda x, n, axis: torch.repeat_interleave(x, n, dim=axis))(v_cache[:, :, Sk - W:, :], rep, axis=1)
        scores = torch.einsum("bhqd,bhkd->bhqk", q, k) * (Dh ** -0.5)
        p = _softmax(scores, axis=-1)
        o = torch.einsum("bhqk,bhkd->bhqd", p, v)
        return (lambda x, *d: x.permute(*d))(o, 0, 2, 1, 3).reshape(B, Sq, Hq * Dh) @ wo

    def _B_ref(x, w1, w2):
        h = torch.einsum("bsd,df->bsf", x, w1)
        h = _silu(h)
        out = torch.einsum("bsf,fd->bsd", h, w2)
        return out

    x = A_x
    h = x + _A_ref(_layernorm(x, axis=-1), A_k_cache, A_v_cache, A_wq, A_wo)
    h2 = h + _B_ref(_layernorm(h, axis=-1), B_w1, B_w2)
    return h2
```

```cpp
#include <cuda_runtime.h>
#include <cuda_bf16.h>
#include <cuda.h>
#include <stdint.h>

namespace {

constexpr int DM = 576, HKV = 16, SK = 8192, WIN = 2048, DH = 128, FF = 4608, QD = 4096;
constexpr int CL = 6;
constexpr int NWARPS = 14;
constexpr int NTHREADS = NWARPS * 32;

constexpr int R1 = 0;
constexpr int WQ_OFF = 90112 - 6 * 8192;
constexpr int R2 = 90112;
constexpr int WO_OFF = R2;
constexpr int W1_OFF = R2 + 49152;
constexpr int INA = R2 + 104448;
constexpr int INB = INA + 6144;
constexpr int INP2 = INB + 6144;
constexpr int INP1 = INP2 + 6912;
constexpr int INML = INP1 + 6912;
constexpr int INST = INML + 1088;
constexpr int XNV = INST + 64;
constexpr int QV = XNV + 192;
constexpr int PVV = QV + 544;
constexpr int OV = PVV + 1408;
constexpr int HV = OV + 512;
constexpr int AV = HV + 192;
constexpr int BARS = AV + 576;
constexpr int SMEM_BYTES = BARS + 64 * 8;
static_assert(SMEM_BYTES <= 232448 - 2048, "smem");

constexpr int B_WQ = 0, B_K = 6, B_V = 17, B_WO = 28, B_W1 = 36, B_W2 = 42, NCHUNK = 51;
constexpr int B_A = 51, B_ML = 52, B_B = 53, B_P2 = 54, B_ST = 55, B_P1 = 56;
constexpr int B_QDONE = 57, B_KDONE = 58, B_PVDONE = 59, B_H = 60, NBAR = 61;

__host__ __device__ constexpr int chunk_bytes(int i) {
    return i < B_WO ? 8192 : i < B_W1 ? 6144 : i < B_W2 ? 9216 : 6144;
}
#define WIN_EARLY 65536
#define LATE_FROM B_W1
#define POLL_SLEEP 0
#define WIN_LATE 40960
__host__ __device__ constexpr int trigger(int i) {
    int w = i < LATE_FROM ? WIN_EARLY : WIN_LATE, s = 0, j = i;
    while (j >= 0 && s + chunk_bytes(j) <= w) { s += chunk_bytes(j); j--; }
    return j;
}

constexpr float NCONTRIB = 48.f;
__device__ __align__(1024) float g_acc[2][2][CL][128];
__device__ uint32_t g_epoch;

#define TLOG(i) do {} while (0)
#define TFLUSH() do {} while (0)
#define TLOG1(i) do {} while (0)

__device__ __forceinline__ void mbar_init(uint32_t a, uint32_t c) {
    asm volatile("mbarrier.init.shared::cta.b64 [%0], %1;" ::"r"(a), "r"(c) : "memory");
}
__device__ __forceinline__ void mbar_expect(uint32_t a, uint32_t b) {
    asm volatile("mbarrier.arrive.expect_tx.shared::cta.b64 _, [%0], %1;" ::"r"(a), "r"(b) : "memory");
}
__device__ __forceinline__ void mbar_arrive(uint32_t a) {
    asm volatile("mbarrier.arrive.shared::cta.b64 _, [%0];" ::"r"(a) : "memory");
}
constexpr int SPIN_LIMIT = 1 << 22;
__device__ __forceinline__ void mbar_wait(uint32_t a) {
    uint32_t ok;
    int it = 0;
    do {
        asm volatile("{\n.reg .pred p;\nmbarrier.try_wait.parity.shared::cta.b64 p, [%1], 0;\nselp.u32 %0, 1, 0, p;\n}"
                     : "=r"(ok) : "r"(a) : "memory");
        if (++it > SPIN_LIMIT) __trap();
    } while (!ok);
}
__device__ __forceinline__ void mbar_wait_cl(uint32_t a) {
    uint32_t ok;
    int it = 0;
    do {
        asm volatile("{\n.reg .pred p;\nmbarrier.try_wait.parity.acquire.cluster.shared::cta.b64 p, [%1], 0;\nselp.u32 %0, 1, 0, p;\n}"
                     : "=r"(ok) : "r"(a) : "memory");
        if (++it > SPIN_LIMIT) __trap();
    } while (!ok);
}
__device__ __forceinline__ void tma3(uint32_t dst, const CUtensorMap* m, int c1, int c2, uint32_t bar) {
    asm volatile("cp.async.bulk.tensor.3d.shared::cluster.global.mbarrier::complete_tx::bytes [%0], [%1, {%2, %3, %4}], [%5];"
                 ::"r"(dst), "l"(m), "r"(0), "r"(c1), "r"(c2), "r"(bar) : "memory");
}
__device__ __forceinline__ void ldsm4(uint32_t (&r)[4], uint32_t a) {
    asm volatile("ldmatrix.sync.aligned.m8n8.x4.shared.b16 {%0,%1,%2,%3}, [%4];"
                 : "=r"(r[0]), "=r"(r[1]), "=r"(r[2]), "=r"(r[3]) : "r"(a) : "memory");
}
__device__ __forceinline__ void ldsm4t(uint32_t (&r)[4], uint32_t a) {
    asm volatile("ldmatrix.sync.aligned.m8n8.x4.trans.shared.b16 {%0,%1,%2,%3}, [%4];"
                 : "=r"(r[0]), "=r"(r[1]), "=r"(r[2]), "=r"(r[3]) : "r"(a) : "memory");
}
__device__ __forceinline__ void mma(float (&c)[4], const uint32_t (&a)[4], uint32_t b0, uint32_t b1) {
    asm("mma.sync.aligned.m16n8k16.row.col.f32.bf16.bf16.f32 {%0,%1,%2,%3}, {%4,%5,%6,%7}, {%8,%9}, {%0,%1,%2,%3};"
        : "+f"(c[0]), "+f"(c[1]), "+f"(c[2]), "+f"(c[3])
        : "r"(a[0]), "r"(a[1]), "r"(a[2]), "r"(a[3]), "r"(b0), "r"(b1));
}
__device__ __forceinline__ uint32_t mapa(uint32_t a, uint32_t cta) {
    uint32_t r;
    asm("mapa.shared::cluster.u32 %0, %1, %2;" : "=r"(r) : "r"(a), "r"(cta));
    return r;
}
__device__ __forceinline__ void st_async4(uint32_t rb, int off, int bar, float a, float b, float c, float d) {
    asm volatile("st.async.weak.shared::cluster.mbarrier::complete_tx::bytes.v4.f32 [%0], {%1,%2,%3,%4}, [%5];"
                 ::"r"(rb + off), "f"(a), "f"(b), "f"(c), "f"(d), "r"(rb + BARS + bar * 8) : "memory");
}
__device__ __forceinline__ void st_async2(uint32_t rb, int off, int bar, float a, float b) {
    asm volatile("st.async.weak.shared::cluster.mbarrier::complete_tx::bytes.v2.f32 [%0], {%1,%2}, [%3];"
                 ::"r"(rb + off), "f"(a), "f"(b), "r"(rb + BARS + bar * 8) : "memory");
}
__device__ __forceinline__ void bar_sync(int id, int n) { asm volatile("bar.sync %0, %1;" ::"r"(id), "r"(n) : "memory"); }
__device__ __forceinline__ void bar_arrive(int id, int n) { asm volatile("bar.arrive %0, %1;" ::"r"(id), "r"(n) : "memory"); }
__device__ __forceinline__ void cluster_wait() { asm volatile("barrier.cluster.wait.acquire.aligned;" ::: "memory"); }
__device__ __forceinline__ float4 lds128(uint32_t a) {
    float4 v;
    asm volatile("ld.shared.v4.f32 {%0,%1,%2,%3}, [%4];" : "=f"(v.x), "=f"(v.y), "=f"(v.z), "=f"(v.w) : "r"(a) : "memory");
    return v;
}
__device__ __forceinline__ float2 lds64(uint32_t a) {
    float2 v;
    asm volatile("ld.shared.v2.f32 {%0,%1}, [%2];" : "=f"(v.x), "=f"(v.y) : "r"(a) : "memory");
    return v;
}
__device__ __forceinline__ void sts16(uint32_t a, float v) {
    asm volatile("st.shared.u16 [%0], %1;" ::"r"(a), "h"(__bfloat16_as_ushort(__float2bfloat16_rn(v))) : "memory");
}
__device__ __forceinline__ float bfr(float v) { return __bfloat162float(__float2bfloat16_rn(v)); }
__device__ __forceinline__ float bf_lo(uint32_t w) { return __uint_as_float(w << 16); }
__device__ __forceinline__ float bf_hi(uint32_t w) { return __uint_as_float(w & 0xffff0000u); }
__device__ __forceinline__ uint32_t pack_bf(float lo, float hi) {
    __nv_bfloat162 v = __floats2bfloat162_rn(lo, hi);
    return *reinterpret_cast<uint32_t*>(&v);
}
__device__ __forceinline__ float wsum(float v) {
#pragma unroll
    for (int o = 16; o; o >>= 1) v += __shfl_xor_sync(0xffffffffu, v, o);
    return v;
}
__device__ __forceinline__ float wmax(float v) {
#pragma unroll
    for (int o = 16; o; o >>= 1) v = fmaxf(v, __shfl_xor_sync(0xffffffffu, v, o));
    return v;
}
__device__ __forceinline__ uint32_t sw64(uint32_t a) { return a ^ ((a >> 3) & 0x30u); }
__device__ __forceinline__ uint32_t sw128(uint32_t a) { return a ^ ((a >> 3) & 0x70u); }

__device__ __forceinline__ float lds_bf(uint32_t a) {
    uint16_t v;
    asm volatile("ld.shared.u16 %0, [%1];" : "=h"(v) : "r"(a) : "memory");
    return __uint_as_float((uint32_t)v << 16);
}
__device__ __forceinline__ float4 sum6(uint32_t a, int stride) {
    float4 v[CL];
#pragma unroll
    for (int s = 0; s < CL; s++) v[s] = lds128(a + s * stride);
    return make_float4(((v[0].x + v[1].x) + (v[2].x + v[3].x)) + (v[4].x + v[5].x), ((v[0].y + v[1].y) + (v[2].y + v[3].y)) + (v[4].y + v[5].y),
                       ((v[0].z + v[1].z) + (v[2].z + v[3].z)) + (v[4].z + v[5].z), ((v[0].w + v[1].w) + (v[2].w + v[3].w)) + (v[4].w + v[5].w));
}
__device__ __forceinline__ float2 sum6h(uint32_t a, int stride) {
    float2 v[CL];
#pragma unroll
    for (int s = 0; s < CL; s++) v[s] = lds64(a + s * stride);
    return make_float2(((v[0].x + v[1].x) + (v[2].x + v[3].x)) + (v[4].x + v[5].x), ((v[0].y + v[1].y) + (v[2].y + v[3].y)) + (v[4].y + v[5].y));
}

template <int I, int END>
__device__ __forceinline__ void produce(uint32_t sb, const CUtensorMap* mq, const CUtensorMap* mk, const CUtensorMap* mv, const CUtensorMap* mo,
                                        const CUtensorMap* m1, const CUtensorMap* m2, int c, int r, int key0, int nk) {
    if constexpr (I < END) {
        constexpr int T = trigger(I);
        const uint32_t bar = sb + BARS + I * 8;
        if constexpr (T >= 0 && (I == 0 || T != trigger(I - 1))) mbar_wait(sb + BARS + T * 8);
        if constexpr (I == B_V + WQ_OFF / 8192) mbar_wait(sb + BARS + B_QDONE * 8);
        if constexpr (I == B_WO) mbar_wait(sb + BARS + B_KDONE * 8);
        if constexpr (I == B_W2) mbar_wait(sb + BARS + B_PVDONE * 8);
        if constexpr (I < B_K) {
            tma3(sb + WQ_OFF + I * 8192, mq, 96 * r + I * 16, 4 * c, bar);
        } else if constexpr (I < B_V) {
            if (I - B_K < nk) tma3(sb + R2 + (I - B_K) * 8192, mk, 0, key0 + (I - B_K) * 32, bar);
        } else if constexpr (I < B_WO) {
            if (I - B_V < nk) tma3(sb + R1 + (I - B_V) * 8192, mv, 0, key0 + (I - B_V) * 32, bar);
        } else if constexpr (I < B_W1) {
            tma3(sb + WO_OFF + (I - B_WO) * 6144, mo, 3 * r, 256 * c + (I - B_WO) * 32, bar);
        } else if constexpr (I < B_W2) {
            tma3(sb + W1_OFF + (I - B_W1) * 9216, m1, 9 * c, 96 * r + (I - B_W1) * 16, bar);
        } else {
            tma3(sb + R1 + (I - B_W2) * 6144, m2, 3 * r, 288 * c + (I - B_W2) * 32, bar);
        }
        produce<I + 1, END>(sb, mq, mk, mv, mo, m1, m2, c, r, key0, nk);
    }
}

__global__ void __cluster_dims__(CL, 1, 1) __launch_bounds__(NTHREADS, 1)
decode_layer_kernel(const __nv_bfloat16* __restrict__ x, const __nv_bfloat16* __restrict__ wq, __nv_bfloat16* __restrict__ out,
                    const __grid_constant__ CUtensorMap mq, const __grid_constant__ CUtensorMap mk, const __grid_constant__ CUtensorMap mv,
                    const __grid_constant__ CUtensorMap mo, const __grid_constant__ CUtensorMap m1,
                    const __grid_constant__ CUtensorMap m2) {
    extern __shared__ __align__(1024) unsigned char smem[];
    const int tid = threadIdx.x, lane = tid & 31;
    const int c = blockIdx.x / CL, r = blockIdx.x % CL;
    if (tid >= 384 && tid < 393) asm volatile("prefetch.global.L2 [%0];" ::"l"(x + (tid - 384) * 64));
    if (tid < 384)
        asm volatile("prefetch.global.L2 [%0];" ::"l"(reinterpret_cast<const char*>(wq) + (size_t)(96 * r + (tid >> 2)) * (QD * 2) + c * 512 + (tid & 3) * 128));
    const int warp = __shfl_sync(0xffffffffu, tid >> 5, 0);
    const uint32_t sb = (uint32_t)__cvta_generic_to_shared(smem);
    const int nk = r < 4 ? 11 : 10;
    const int g = lane >> 2, t = lane & 3;

    if (warp == 13) {
        const int key0 = c * SK + (SK - WIN) + (r < 4 ? 352 * r : 1408 + 320 * (r - 4));
        if (lane == 0) {
            asm volatile("prefetch.tensormap [%0];" ::"l"(&mq) : "memory");
            TLOG1(1);
#pragma unroll
            for (int b = 0; b < B_K; b++) {
                mbar_init(sb + BARS + b * 8, 1);
                mbar_expect(sb + BARS + b * 8, chunk_bytes(b));
            }
            asm volatile("fence.mbarrier_init.release.cluster;" ::: "memory");
            TLOG1(2);
            produce<0, B_K>(sb, &mq, &mk, &mv, &mo, &m1, &m2, c, r, key0, nk);
            asm volatile("prefetch.tensormap [%0];" ::"l"(&mk) : "memory");
            asm volatile("prefetch.tensormap [%0];" ::"l"(&mv) : "memory");
            asm volatile("prefetch.tensormap [%0];" ::"l"(&mo) : "memory");
            asm volatile("prefetch.tensormap [%0];" ::"l"(&m1) : "memory");
            asm volatile("prefetch.tensormap [%0];" ::"l"(&m2) : "memory");
            TLOG1(3);
        }
        __syncthreads();
        asm volatile("barrier.cluster.arrive.relaxed.aligned;" ::: "memory");
        TLOG(4);
        if (lane == 0) produce<B_K, NCHUNK>(sb, &mq, &mk, &mv, &mo, &m1, &m2, c, r, key0, nk);
        __syncwarp();
        TLOG(0);
        cluster_wait();
        TFLUSH();
        return;
    }

    if (warp == 12) {
        const uint32_t* x32 = reinterpret_cast<const uint32_t*>(x);
        uint32_t xr[9];
#pragma unroll
        for (int i = 0; i < 9; i++) xr[i] = __ldg(x32 + lane + 32 * i);
        const uint32_t xs0 = __ldg(x32 + 48 * r + lane), xs1 = __ldg(x32 + 48 * r + 32 + (lane & 15));
        const int col = 48 * (lane >> 4) + (lane & 15);
        const float x0 = __bfloat162float(x[96 * r + col]), x1 = __bfloat162float(x[96 * r + col + 16]), x2 = __bfloat162float(x[96 * r + col + 32]);
        __syncthreads();
        asm volatile("barrier.cluster.arrive.relaxed.aligned;" ::: "memory");
        float s = 0.f;
#pragma unroll
        for (int i = 0; i < 9; i++) s += bf_lo(xr[i]) + bf_hi(xr[i]);
        TLOG(2);
        const float mean = wsum(s) / DM;
        float v = 0.f;
#pragma unroll
        for (int i = 0; i < 9; i++) {
            const float a = bf_lo(xr[i]) - mean, b = bf_hi(xr[i]) - mean;
            v += a * a + b * b;
        }
        const float mb = bfr(mean), sd = bfr(sqrtf(bfr(bfr(wsum(v) / DM) + 1e-5f)));
        asm volatile("st.shared.u32 [%0], %1;" ::"r"(sb + XNV + lane * 4),
                     "r"(pack_bf(bfr(bf_lo(xs0) - mb) / sd, bfr(bf_hi(xs0) - mb) / sd)) : "memory");
        asm volatile("st.shared.u32 [%0], %1;" ::"r"(sb + XNV + 128 + (lane & 15) * 4),
                     "r"(pack_bf(bfr(bf_lo(xs1) - mb) / sd, bfr(bf_hi(xs1) - mb) / sd)) : "memory");
        bar_arrive(1, 288);
        TLOG(0);
        uint32_t epoch;
        asm volatile("ld.global.u32 %0, [%1];" : "=r"(epoch) : "l"(&g_epoch) : "memory");
        const uint32_t par = epoch & 1u;
        if (c == 0) {
            *reinterpret_cast<float4*>(&g_acc[par ^ 1][0][r][lane * 4]) = make_float4(0.f, 0.f, 0.f, 0.f);
            *reinterpret_cast<float4*>(&g_acc[par ^ 1][1][r][lane * 4]) = make_float4(0.f, 0.f, 0.f, 0.f);
        }
        cluster_wait();
        mbar_wait(sb + BARS + B_B * 8);
        float a0, a1, a2, n;
        int it = 0;
        do {
            asm volatile("ld.relaxed.gpu.global.v4.f32 {%0,%1,%2,%3}, [%4];" : "=f"(a0), "=f"(a1), "=f"(a2), "=f"(n) : "l"(&g_acc[par][0][r][lane * 4]) : "memory");
            if (++it > SPIN_LIMIT) __trap();
        } while (n != NCONTRIB);
        const float h0 = bfr(x0 + bfr(a0)), h1 = bfr(x1 + bfr(a1)), h2 = bfr(x2 + bfr(a2));
        sts16(sb + HV + col * 2, h0); sts16(sb + HV + col * 2 + 32, h1); sts16(sb + HV + col * 2 + 64, h2);
        __syncwarp();
        if (lane == 0) mbar_arrive(sb + BARS + B_H * 8);
        TLOG(9);
        const float ctr = __shfl_sync(0xffffffffu, h0, 0);
        const float d0 = h0 - ctr, d1 = h1 - ctr, d2 = h2 - ctr;
        float s1 = d0 + d1 + d2, s2 = d0 * d0 + d1 * d1 + d2 * d2;
#pragma unroll
        for (int o = 16; o; o >>= 1) {
            s1 += __shfl_xor_sync(0xffffffffu, s1, o);
            s2 += __shfl_xor_sync(0xffffffffu, s2, o);
        }
        if (lane < CL) st_async2(mapa(sb, lane), INST + r * 8, B_ST, ctr + s1 * (1.f / 96.f), s2 - s1 * s1 * (1.f / 96.f));
        TLOG(10);
        TFLUSH();
        return;
    }

    if (warp < 11) {
        const int b0 = B_K + 5 * warp;
        if (lane == 0) {
#pragma unroll
            for (int i = 0; i < 5; i++) {
                const int b = b0 + i;
                mbar_init(sb + BARS + b * 8, b == B_KDONE ? 11 : (b == B_QDONE || b == B_PVDONE) ? 8 : 1);
            }
        }
        __syncwarp();
        const int b = b0 + lane;
        if (lane < 5 && b < B_QDONE) {
            const uint32_t bytes = b < NCHUNK ? chunk_bytes(b) : b == B_ML ? 1056 : b == B_ST ? 48 : (b == B_A || b == B_B) ? 6144 : 6912;
            mbar_expect(sb + BARS + b * 8, (nk == 10 && (b == B_K + 10 || b == B_V + 10)) ? 0 : bytes);
        }
        asm volatile("fence.mbarrier_init.release.cluster;" ::: "memory");
    }
    TLOG(14);
    __syncthreads();
    asm volatile("barrier.cluster.arrive.relaxed.aligned;" ::: "memory");
    TLOG(7);
    uint32_t epoch = 0;
    if (warp < 6) asm volatile("ld.global.u32 %0, [%1];" : "=r"(epoch) : "l"(&g_epoch) : "memory");
    const uint32_t rb0 = mapa(sb, t), rb1 = mapa(sb, 4 + (t & 1));
    const int trow = (lane & 7) + 8 * (lane >> 4), tcol = (lane >> 3) & 1;

    if (warp < 8) {
        bar_sync(1, 288);
        uint32_t b[3][4];
#pragma unroll
        for (int u = 0; u < 3; u++) ldsm4(b[u], sb + XNV + u * 64 + (lane >> 3) * 16);
        float acc[2][4] = {};
#pragma unroll
        for (int s = 0; s < 6; s++) {
            mbar_wait(sb + BARS + (B_WQ + s) * 8);
#pragma unroll
            for (int n = 0; n < 2; n++) {
                uint32_t a[4];
                ldsm4t(a, sb + WQ_OFF + s * 8192 + (warp >> 1) * 2048 + sw128(trow * 128 + (4 * (warp & 1) + 2 * n + tcol) * 16));
                mma(acc[n], a, b[s >> 1][(s & 1) * 2], b[s >> 1][(s & 1) * 2 + 1]);
            }
        }
        TLOG(0);
        cluster_wait();
        const int off = INA + r * 1024 + (warp * 8 + g) * 16;
        st_async4(rb0, off, B_A, acc[0][0], acc[0][2], acc[1][0], acc[1][2]);
        if (t < 2) st_async4(rb1, off, B_A, acc[0][0], acc[0][2], acc[1][0], acc[1][2]);
        if (lane == 0) mbar_arrive(sb + BARS + B_QDONE * 8);
    } else {
        cluster_wait();
        if (warp < 10) {
            const int i = tid - 256;
            mbar_wait_cl(sb + BARS + B_A * 8);
            const float4 v = sum6(sb + INA + i * 16, 1024);
            const int n = 32 * (i >> 3) + (i & 7);
            const uint32_t a = sb + QV + (n >> 7) * 272 + (n & 127) * 2;
            sts16(a, v.x); sts16(a + 16, v.y); sts16(a + 32, v.z); sts16(a + 48, v.w);
        }
    }

    if (warp < 11) {
        bar_sync(2, 352);
        TLOG(1);
        float s0 = -INFINITY, s1 = -INFINITY, m0 = -INFINITY, m1v = -INFINITY, e0 = 0.f, e1 = 0.f, l0 = 0.f, l1 = 0.f;
        if (warp < nk) {
            uint32_t b[4][4];
#pragma unroll
            for (int u = 0; u < 4; u++) ldsm4(b[u], sb + QV + (lane & 1) * 272 + (4 * u + (lane >> 3)) * 16);
            float acc[2][4] = {};
            mbar_wait(sb + BARS + (B_K + warp) * 8);
            TLOG(2);
            const uint32_t krow = ((lane & 7) + 8 * ((lane >> 3) & 1)) * 256 + (lane >> 4) * 16;
#pragma unroll
            for (int s = 0; s < 8; s++) {
#pragma unroll
                for (int n = 0; n < 2; n++) {
                    uint32_t a[4];
                    ldsm4(a, sb + R2 + warp * 8192 + sw128(krow + n * 4096 + s * 32));
                    mma(acc[n], a, b[s >> 1][(s & 1) * 2], b[s >> 1][(s & 1) * 2 + 1]);
                }
            }
            const float r0 = t == 0 ? acc[0][0] : t == 1 ? acc[0][2] : t == 2 ? acc[1][0] : acc[1][2];
            const float r1 = t == 0 ? acc[0][1] : t == 1 ? acc[0][3] : t == 2 ? acc[1][1] : acc[1][3];
            s0 = bfr(bfr(r0) * 0.08838834764831845f);
            s1 = bfr(bfr(r1) * 0.08838834764831845f);
            m0 = wmax(s0); m1v = wmax(s1);
            e0 = __expf(s0 - m0); e1 = __expf(s1 - m1v);
            l0 = wsum(e0); l1 = wsum(e1);
        }
        if (lane == 0) mbar_arrive(sb + BARS + B_KDONE * 8);
        if (lane < CL) st_async4(mapa(sb, lane), INML + (r * 11 + warp) * 16, B_ML, m0, m1v, l0, l1);
        mbar_wait_cl(sb + BARS + B_ML * 8);
        if (warp < nk) {
            const float4 u0 = lds128(sb + INML + lane * 16), u1 = lds128(sb + INML + (lane + 32) * 16);
            float4 u2 = make_float4(-INFINITY, -INFINITY, 0.f, 0.f);
            if (lane < 2) u2 = lds128(sb + INML + (lane + 64) * 16);
            const float M0 = wmax(fmaxf(fmaxf(u0.x, u1.x), u2.x)), M1 = wmax(fmaxf(fmaxf(u0.y, u1.y), u2.y));
            const float L0 = wsum(u0.z * __expf(u0.x - M0) + u1.z * __expf(u1.x - M0) + u2.z * __expf(u2.x - M0));
            const float L1 = wsum(u0.w * __expf(u0.y - M1) + u1.w * __expf(u1.y - M1) + u2.w * __expf(u2.y - M1));
            const uint32_t a = sb + PVV + (32 * warp + 8 * t + g) * 2;
            sts16(a, e0 * (__expf(m0 - M0) / L0));
            sts16(a + 704, e1 * (__expf(m1v - M1) / L1));
        }
        TLOG(3);
    }

    if (warp < 8) {
        bar_sync(3, 352);
        float acc[2][4] = {};
        const uint32_t vrow = trow * 256 + (2 * warp + tcol) * 16;
#pragma unroll
        for (int j = 0; j < 11; j++) {
            if (j < nk) {
                uint32_t b[4], a0[4], a1[4];
                ldsm4(b, sb + PVV + (lane & 1) * 704 + j * 64 + (lane >> 3) * 16);
                mbar_wait(sb + BARS + (B_V + j) * 8);
                ldsm4t(a0, sb + R1 + j * 8192 + sw128(vrow));
                ldsm4t(a1, sb + R1 + j * 8192 + 4096 + sw128(vrow));
                mma(acc[0], a0, b[0], b[1]);
                mma(acc[1], a1, b[2], b[3]);
            }
        }
        const float v0 = acc[0][0] + acc[1][0], v1 = acc[0][1] + acc[1][1], v2 = acc[0][2] + acc[1][2], v3 = acc[0][3] + acc[1][3];
        const int off = INB + r * 1024 + (warp * 8 + g) * 16;
        st_async4(rb0, off, B_B, v0, v1, v2, v3);
        if (t < 2) st_async4(rb1, off, B_B, v0, v1, v2, v3);
        if (lane == 0) mbar_arrive(sb + BARS + B_PVDONE * 8);
        TLOG(4);
    } else if (warp < 11) {
        bar_arrive(3, 352);
        if (warp < 10) {
            const int i = tid - 256;
            mbar_wait_cl(sb + BARS + B_B * 8);
            const float4 v = sum6(sb + INB + i * 16, 1024);
            const uint32_t a = sb + OV + (16 * (i >> 3) + (i & 7)) * 2;
            sts16(a, v.x); sts16(a + 256, v.y); sts16(a + 16, v.z); sts16(a + 272, v.w);
            bar_arrive(4, 256);
            TLOG(5);
        }
    }

    if (warp < 6) {
        const int half = warp & 1, kg = warp >> 1;
        const uint32_t wrow = trow * 192 + (6 * half + tcol) * 16;
        const uint32_t wa[3] = {sw64(wrow), sw64(wrow + 32), sw64(wrow + 64)};
        float* accC = &g_acc[epoch & 1u][0][r][(half * 16 + (t & 1) * 8 + g) * 4];
        {
            bar_sync(4, 256);
            TLOG(5);
            float acc[3][2][4] = {};
#pragma unroll
            for (int i = 0; i < 3; i++) {
                const int j = kg + 3 * i;
                if (j < 8) {
                    uint32_t b[4];
                    ldsm4(b, sb + OV + j * 64 + (lane >> 3) * 16);
                    mbar_wait(sb + BARS + (B_WO + j) * 8);
#pragma unroll
                    for (int n = 0; n < 3; n++) {
                        uint32_t a0[4], a1[4];
                        ldsm4t(a0, sb + WO_OFF + j * 6144 + wa[n]);
                        ldsm4t(a1, sb + WO_OFF + j * 6144 + 3072 + wa[n]);
                        mma(acc[n][0], a0, b[0], b[1]);
                        mma(acc[n][1], a1, b[2], b[3]);
                    }
                }
            }
            float v[3];
#pragma unroll
            for (int n = 0; n < 3; n++) v[n] = t == 0 ? acc[n][0][0] + acc[n][1][0] : acc[n][0][2] + acc[n][1][2];
            if (t < 2)
                asm volatile("red.relaxed.gpu.global.add.v4.f32 [%0], {%1,%2,%3,%4};" ::"l"(accC), "f"(v[0]), "f"(v[1]), "f"(v[2]), "f"(1.f) : "memory");
            TLOG(6);
        }
        uint32_t a[2][3][2][4];
#pragma unroll
        for (int i = 0; i < 2; i++) {
            const int j = kg + 3 * i;
            mbar_wait(sb + BARS + (B_W2 + j) * 8);
#pragma unroll
            for (int n = 0; n < 3; n++) {
                ldsm4t(a[i][n][0], sb + R1 + j * 6144 + wa[n]);
                ldsm4t(a[i][n][1], sb + R1 + j * 6144 + 3072 + wa[n]);
            }
        }
        TLOG(11);
        bar_sync(6, 352);
        TLOG(12);
        float acc[3][2][4] = {};
        uint32_t b[3][4];
#pragma unroll
        for (int i = 0; i < 3; i++) ldsm4(b[i], sb + AV + (kg + 3 * i) * 64 + (lane >> 3) * 16);
        const int col = 48 * half + 8 * (t & 1) + g;
        const float h0 = lds_bf(sb + HV + col * 2), h1 = lds_bf(sb + HV + col * 2 + 32), h2 = lds_bf(sb + HV + col * 2 + 64);
#pragma unroll
        for (int i = 0; i < 2; i++)
#pragma unroll
            for (int n = 0; n < 3; n++) {
                mma(acc[n][0], a[i][n][0], b[i][0], b[i][1]);
                mma(acc[n][1], a[i][n][1], b[i][2], b[i][3]);
            }
        mbar_wait(sb + BARS + (B_W2 + kg + 6) * 8);
#pragma unroll
        for (int n = 0; n < 3; n++) {
            uint32_t a0[4], a1[4];
            ldsm4t(a0, sb + R1 + (kg + 6) * 6144 + wa[n]);
            ldsm4t(a1, sb + R1 + (kg + 6) * 6144 + 3072 + wa[n]);
            mma(acc[n][0], a0, b[2][0], b[2][1]);
            mma(acc[n][1], a1, b[2][2], b[2][3]);
        }
        TLOG(13);
        if (t < 2) {
            float v[3], o[4];
#pragma unroll
            for (int n = 0; n < 3; n++) v[n] = t == 0 ? acc[n][0][0] + acc[n][1][0] : acc[n][0][2] + acc[n][1][2];
            asm volatile("atom.relaxed.gpu.global.add.v4.f32 {%0,%1,%2,%3}, [%4], {%5,%6,%7,%8};"
                         : "=f"(o[0]), "=f"(o[1]), "=f"(o[2]), "=f"(o[3])
                         : "l"(accC + CL * 128), "f"(v[0]), "f"(v[1]), "f"(v[2]), "f"(1.f) : "memory");
            if (o[3] == NCONTRIB - 1.f) {
                __nv_bfloat16* po = out + 96 * r + col;
                po[0] = __float2bfloat16_rn(h0 + bfr(o[0] + v[0]));
                po[16] = __float2bfloat16_rn(h1 + bfr(o[1] + v[1]));
                po[32] = __float2bfloat16_rn(h2 + bfr(o[2] + v[2]));
                if (r == 0 && col == 0) g_epoch = epoch + 1;
            }
        }
        __syncwarp();
        TLOG(8);
    } else {
        {
            const int w = warp - 6;
            uint32_t a[3][6][4];
            float cs[3][4] = {};
            const uint32_t arow = trow * 576 + (6 * w + tcol) * 16;
#pragma unroll
            for (int s = 0; s < 6; s++) {
                mbar_wait(sb + BARS + (B_W1 + s) * 8);
#pragma unroll
                for (int n = 0; n < 3; n++) {
                    ldsm4t(a[n][s], sb + W1_OFF + s * 9216 + sw64(arow + n * 32));
                    mma(cs[n], a[n][s], 0x3f803f80u, 0x3f803f80u);
                }
            }
            const int off4 = r * 1152 + (w * 8 + g) * 16, off2 = r * 1152 + 768 + (w * 8 + g) * 8;
            st_async4(rb0, INP2 + off4, B_P2, cs[0][0], cs[0][2], cs[1][0], cs[1][2]);
            st_async2(rb0, INP2 + off2, B_P2, cs[2][0], cs[2][2]);
            if (t < 2) {
                st_async4(rb1, INP2 + off4, B_P2, cs[0][0], cs[0][2], cs[1][0], cs[1][2]);
                st_async2(rb1, INP2 + off2, B_P2, cs[2][0], cs[2][2]);
            }
            TLOG(8);
            mbar_wait(sb + BARS + B_H * 8);
            TLOG(9);
            float p[3][2][4] = {};
#pragma unroll
            for (int u = 0; u < 3; u++) {
                uint32_t b[4];
                ldsm4(b, sb + HV + u * 64 + (lane >> 3) * 16);
#pragma unroll
                for (int n = 0; n < 3; n++) {
                    mma(p[n][0], a[n][2 * u], b[0], b[1]);
                    mma(p[n][1], a[n][2 * u + 1], b[2], b[3]);
                }
            }
            float v[3][2];
#pragma unroll
            for (int n = 0; n < 3; n++) { v[n][0] = p[n][0][0] + p[n][1][0]; v[n][1] = p[n][0][2] + p[n][1][2]; }
            st_async4(rb0, INP1 + off4, B_P1, v[0][0], v[0][1], v[1][0], v[1][1]);
            st_async2(rb0, INP1 + off2, B_P1, v[2][0], v[2][1]);
            if (t < 2) {
                st_async4(rb1, INP1 + off4, B_P1, v[0][0], v[0][1], v[1][0], v[1][1]);
                st_async2(rb1, INP1 + off2, B_P1, v[2][0], v[2][1]);
            }
            TLOG(10);
        }
        if (warp < 11) {
            const int i = min(tid - 192, 143);
            mbar_wait_cl(sb + BARS + B_P2 * 8);
            const float2 cs = sum6h(sb + INP2 + i * 8, 1152);
            mbar_wait_cl(sb + BARS + B_ST * 8);
            const float4 u0 = lds128(sb + INST), u1 = lds128(sb + INST + 16), u2 = lds128(sb + INST + 32);
            const float mean = ((u0.x + u0.z) + (u1.x + u1.z) + (u2.x + u2.z)) * (1.f / 6.f);
            const float d0 = u0.x - mean, d1 = u0.z - mean, d2 = u1.x - mean, d3 = u1.z - mean, d4 = u2.x - mean, d5 = u2.z - mean;
            const float var = (((u0.y + u0.w) + (u1.y + u1.w) + (u2.y + u2.w)) +
                               96.f * ((d0 * d0 + d1 * d1) + (d2 * d2 + d3 * d3) + (d4 * d4 + d5 * d5))) * (1.f / DM);
            const float mb = bfr(mean), rs = 1.f / bfr(sqrtf(bfr(bfr(var) + 1e-5f)));
            mbar_wait_cl(sb + BARS + B_P1 * 8);
            TLOG(11);
            const float2 p = sum6h(sb + INP1 + i * 8, 1152);
            const float y0 = bfr((p.x - mb * cs.x) * rs), y1 = bfr((p.y - mb * cs.y) * rs);
            const uint32_t a = sb + AV + (i < 96 ? 48 * (i >> 4) + 16 * (i & 1) + ((i >> 1) & 7) : 48 * ((i - 96) >> 3) + 32 + (i & 7)) * 2;
            sts16(a, __fdividef(y0, 1.f + __expf(-y0)));
            sts16(a + 16, __fdividef(y1, 1.f + __expf(-y1)));
            bar_arrive(6, 352);
            TLOG(12);
        }
    }
    TFLUSH();
}

__device__ float f_q[QD], f_o[QD], f_h[DM], f_a[FF];

__device__ __forceinline__ float block_sum(float v, float* red) {
    v = wsum(v);
    __syncthreads();
    if ((threadIdx.x & 31) == 0) red[threadIdx.x >> 5] = v;
    __syncthreads();
    float s = 0.f;
    for (int i = 0; i < (int)(blockDim.x >> 5); i++) s += red[i];
    return s;
}
__device__ void fb_ln(const __nv_bfloat16* xb, const float* xf, float* xn, float* red) {
    float s = 0.f;
    for (int i = threadIdx.x; i < DM; i += blockDim.x) { xn[i] = xb ? __bfloat162float(xb[i]) : xf[i]; s += xn[i]; }
    const float mean = block_sum(s, red) / DM;
    float v = 0.f;
    for (int i = threadIdx.x; i < DM; i += blockDim.x) v += (xn[i] - mean) * (xn[i] - mean);
    const float sd = bfr(sqrtf(bfr(bfr(block_sum(v, red) / DM) + 1e-5f))), mb = bfr(mean);
    for (int i = threadIdx.x; i < DM; i += blockDim.x) xn[i] = bfr(bfr(xn[i] - mb) / sd);
    __syncthreads();
}
__global__ void fb_ln_gemv(const __nv_bfloat16* x, const __nv_bfloat16* w, int n, int mode) {
    __shared__ float xn[DM], red[8];
    fb_ln(mode == 0 ? x : nullptr, f_h, xn, red);
    const int j = blockIdx.x * blockDim.x + threadIdx.x;
    float s = 0.f;
    for (int k = 0; k < DM; k++) s += xn[k] * __bfloat162float(w[(size_t)k * n + j]);
    s = bfr(s);
    if (mode == 0) f_q[j] = s; else f_a[j] = bfr(s / (1.f + __expf(-s)));
}
__global__ void fb_attn(const __nv_bfloat16* kc, const __nv_bfloat16* vc) {
    __shared__ float p[WIN], red[8];
    const int h = blockIdx.x;
    const size_t base = ((size_t)(h >> 1) * SK + (SK - WIN)) * DH;
    float mx = -INFINITY;
    for (int k = threadIdx.x; k < WIN; k += blockDim.x) {
        float s = 0.f;
        for (int d = 0; d < DH; d++) s += f_q[h * DH + d] * __bfloat162float(kc[base + (size_t)k * DH + d]);
        p[k] = bfr(bfr(s) * 0.08838834764831845f);
        mx = fmaxf(mx, p[k]);
    }
    mx = wmax(mx);
    if ((threadIdx.x & 31) == 0) red[threadIdx.x >> 5] = mx;
    __syncthreads();
    for (int i = 0; i < (int)(blockDim.x >> 5); i++) mx = fmaxf(mx, red[i]);
    float l = 0.f;
    for (int k = threadIdx.x; k < WIN; k += blockDim.x) { p[k] = __expf(p[k] - mx); l += p[k]; }
    l = block_sum(l, red);
    float o = 0.f;
    for (int k = 0; k < WIN; k++) o += bfr(p[k] / l) * __bfloat162float(vc[base + (size_t)k * DH + threadIdx.x]);
    f_o[h * DH + threadIdx.x] = bfr(o);
}
__global__ void fb_out_gemv(const __nv_bfloat16* x, const __nv_bfloat16* w, int rows, int mode, __nv_bfloat16* out) {
    __shared__ float red[8][32];
    const int j = blockIdx.x * 32 + (threadIdx.x & 31);
    const float* v = mode == 0 ? f_o : f_a;
    float s = 0.f;
    for (int k = threadIdx.x >> 5; k < rows; k += 8) s += v[k] * __bfloat162float(w[(size_t)k * DM + j]);
    red[threadIdx.x >> 5][threadIdx.x & 31] = s;
    __syncthreads();
    if (threadIdx.x < 32) {
        s = 0.f;
        for (int i = 0; i < 8; i++) s += red[i][threadIdx.x];
        if (mode == 0) f_h[j] = bfr(__bfloat162float(x[j]) + bfr(s)); else out[j] = __float2bfloat16_rn(f_h[j] + bfr(s));
    }
}

typedef CUresult (*EncodeFn)(CUtensorMap*, CUtensorMapDataType, cuuint32_t, void*, const cuuint64_t*, const cuuint64_t*,
                             const cuuint32_t*, const cuuint32_t*, CUtensorMapInterleave, CUtensorMapSwizzle,
                             CUtensorMapL2promotion, CUtensorMapFloatOOBfill);

bool make_map(EncodeFn enc, CUtensorMap* m, const void* p, int rows, int cols, int inner, int groups, int boxrows,
              bool rows_first = false) {
    const int a = rows_first ? 2 : 1, b = 3 - a;
    cuuint64_t dim[3], str[3];
    cuuint32_t box[3];
    dim[0] = inner; dim[a] = cols / inner; dim[b] = rows;
    str[a - 1] = inner * 2; str[b - 1] = cols * 2;
    box[0] = inner; box[a] = groups; box[b] = boxrows;
    const cuuint32_t es[3] = {1, 1, 1};
#define L2PROMO CU_TENSOR_MAP_L2_PROMOTION_NONE
    return enc(m, CU_TENSOR_MAP_DATA_TYPE_BFLOAT16, 3, const_cast<void*>(p), dim, str, box, es, CU_TENSOR_MAP_INTERLEAVE_NONE,
               inner == 64 ? CU_TENSOR_MAP_SWIZZLE_128B : CU_TENSOR_MAP_SWIZZLE_64B, L2PROMO,
               CU_TENSOR_MAP_FLOAT_OOB_FILL_NONE) == CUDA_SUCCESS;
}

}

extern "C" void kernel_launch(void* const* d_in, const int* in_sizes, int n_in, void* d_out, int out_size) {
    const __nv_bfloat16* x = (const __nv_bfloat16*)d_in[0];
    const __nv_bfloat16* kc = (const __nv_bfloat16*)d_in[1];
    const __nv_bfloat16* vc = (const __nv_bfloat16*)d_in[2];
    const __nv_bfloat16* wq = (const __nv_bfloat16*)d_in[3];
    const __nv_bfloat16* wo = (const __nv_bfloat16*)d_in[4];
    const __nv_bfloat16* w1 = (const __nv_bfloat16*)d_in[6];
    const __nv_bfloat16* w2 = (const __nv_bfloat16*)d_in[7];
    __nv_bfloat16* out = (__nv_bfloat16*)d_out;
    cudaStream_t stream = cudaStreamPerThread;

    static int state = 0;
    static EncodeFn enc = nullptr;
    if (state == 0) {
        state = 2;
        void* fn = nullptr;
        cudaDriverEntryPointQueryResult qr;
        if (cudaGetDriverEntryPoint("cuTensorMapEncodeTiled", &fn, cudaEnableDefault, &qr) == cudaSuccess &&
            qr == cudaDriverEntryPointSuccess && fn &&
            cudaFuncSetAttribute(decode_layer_kernel, cudaFuncAttributeMaxDynamicSharedMemorySize, SMEM_BYTES) == cudaSuccess) {
            enc = (EncodeFn)fn;
            cudaLaunchConfig_t cfg = {};
            cfg.gridDim = dim3(HKV * CL); cfg.blockDim = dim3(NTHREADS); cfg.dynamicSmemBytes = SMEM_BYTES;
            cudaLaunchAttribute at[1];
            at[0].id = cudaLaunchAttributeClusterDimension;
            at[0].val.clusterDim.x = CL; at[0].val.clusterDim.y = 1; at[0].val.clusterDim.z = 1;
            cfg.attrs = at; cfg.numAttrs = 1;
            int nc = 0;
            if (cudaOccupancyMaxActiveClusters(&nc, decode_layer_kernel, &cfg) == cudaSuccess && nc >= HKV) state = 1;
        }
        (void)cudaGetLastError();
    }
    CUtensorMap mq, mk, mv, mo, m1, m2;
    if (state == 1 && make_map(enc, &mq, wq, DM, QD, 64, 4, 16, true) && make_map(enc, &mk, kc, HKV * SK, DH, 64, 2, 32) && make_map(enc, &mv, vc, HKV * SK, DH, 64, 2, 32) &&
        make_map(enc, &mo, wo, QD, DM, 32, 3, 32) && make_map(enc, &m1, w1, DM, FF, 32, 9, 16) &&
        make_map(enc, &m2, w2, FF, DM, 32, 3, 32)) {
        decode_layer_kernel<<<HKV * CL, NTHREADS, SMEM_BYTES, stream>>>(x, wq, out, mq, mk, mv, mo, m1, m2);
        return;
    }
    fb_ln_gemv<<<QD / 128, 128, 0, stream>>>(x, wq, QD, 0);
    fb_attn<<<2 * HKV, 128, 0, stream>>>(kc, vc);
    fb_out_gemv<<<DM / 32, 256, 0, stream>>>(x, wo, QD, 0, out);
    fb_ln_gemv<<<FF / 128, 128, 0, stream>>>(x, w1, FF, 1);
    fb_out_gemv<<<DM / 32, 256, 0, stream>>>(x, w2, FF, 1, out);
}
```

```cpp
#include <cuda_runtime.h>
#include <cuda_bf16.h>
#include <cuda.h>
#include <stdint.h>

namespace {

constexpr int DM = 576, HKV = 16, SK = 8192, WIN = 2048, DH = 128, FF = 4608, QD = 4096;
constexpr int CL = 6;
constexpr int NWARPS = 14;
constexpr int NTHREADS = NWARPS * 32;

constexpr int R1 = 0;
constexpr int WQ_OFF = 90112 - 6 * 8192;
constexpr int R2 = 90112;
constexpr int WO_OFF = R2;
constexpr int W1_OFF = R2 + 49152;
constexpr int INA = R2 + 104448;
constexpr int INB = INA + 6144;
constexpr int INP2 = INB + 6144;
constexpr int INP1 = INP2 + 6912;
constexpr int INML = INP1 + 6912;
constexpr int INST = INML + 1088;
constexpr int XNV = INST + 64;
constexpr int QV = XNV + 192;
constexpr int PVV = QV + 544;
constexpr int OV = PVV + 1408;
constexpr int HV = OV + 512;
constexpr int AV = HV + 192;
constexpr int BARS = AV + 576;
constexpr int SMEM_BYTES = BARS + 64 * 8;
static_assert(SMEM_BYTES <= 232448 - 2048, "smem");

constexpr int B_WQ = 0, B_K = 6, B_V = 17, B_WO = 28, B_W1 = 36, B_W2 = 42, NCHUNK = 51;
constexpr int B_A = 51, B_ML = 52, B_B = 53, B_P2 = 54, B_ST = 55, B_P1 = 56;
constexpr int B_QDONE = 57, B_KDONE = 58, B_PVDONE = 59, B_H = 60, B_AR = 61, NBAR = 62;

__host__ __device__ constexpr int chunk_bytes(int i) {
    return i < B_WO ? 8192 : i < B_W1 ? 6144 : i < B_W2 ? 9216 : 6144;
}
#define NARROW 64, 40, 38, 38, 32
#define WIDE 64, 64, 64, 56, 44
#define PACE_PS 480
#define PACE_T0 600
__host__ __device__ constexpr int by_phase(int i, int k, int v, int o, int a, int b) {
    return 1024 * (i < B_V ? k : i < B_WO ? v : i < B_W1 ? o : i < B_W2 ? a : b);
}
__host__ __device__ constexpr int need_landed(int i, int w) {
    int s = 0, j = i;
    while (j >= 0 && s + chunk_bytes(j) <= w) { s += chunk_bytes(j); j--; }
    return j + 1;
}
__host__ __device__ constexpr int nominal_ns(int i) {
    int cum = -44 * 1024 - (i >= B_V ? 2731 : 0) - (i >= B_WO ? 2731 : 0);
    for (int j = 0; j <= i; j++) cum += chunk_bytes(j);
    return PACE_T0 + cum / 16 * PACE_PS / 1000;
}

constexpr float N_ATT = 48.f;
constexpr float N_OUT = 49.f;
__device__ __align__(1024) float g_acc[2][2][CL][128];
__device__ uint32_t g_epoch;

#define TLOG(i) do {} while (0)
#define TFLUSH() do {} while (0)
#define TLOG1(i) do {} while (0)

__device__ __forceinline__ void mbar_init(uint32_t a, uint32_t c) {
    asm volatile("mbarrier.init.shared::cta.b64 [%0], %1;" ::"r"(a), "r"(c) : "memory");
}
__device__ __forceinline__ void mbar_expect(uint32_t a, uint32_t b) {
    asm volatile("mbarrier.arrive.expect_tx.shared::cta.b64 _, [%0], %1;" ::"r"(a), "r"(b) : "memory");
}
__device__ __forceinline__ void mbar_arrive(uint32_t a) {
    asm volatile("mbarrier.arrive.shared::cta.b64 _, [%0];" ::"r"(a) : "memory");
}
constexpr int SPIN_LIMIT = 1 << 21;
__device__ __forceinline__ void mbar_wait(uint32_t a) {
    uint32_t ok;
    int it = 0;
    do {
        asm volatile("{\n.reg .pred p;\nmbarrier.try_wait.parity.shared::cta.b64 p, [%1], 0;\nselp.u32 %0, 1, 0, p;\n}"
                     : "=r"(ok) : "r"(a) : "memory");
        if (++it > SPIN_LIMIT) __trap();
    } while (!ok);
}
__device__ __forceinline__ void mbar_spin(uint32_t a) {
    uint32_t ok;
    int it = 0;
    do {
        asm volatile("{\n.reg .pred p;\nmbarrier.test_wait.parity.shared::cta.b64 p, [%1], 0;\nselp.u32 %0, 1, 0, p;\n}"
                     : "=r"(ok) : "r"(a) : "memory");
        if (++it > 8 * SPIN_LIMIT) __trap();
    } while (!ok);
}
__device__ __forceinline__ float2 ln_stats(uint32_t a) {
    float4 u[3];
#pragma unroll
    for (int i = 0; i < 3; i++)
        asm volatile("ld.shared.v4.f32 {%0,%1,%2,%3}, [%4];" : "=f"(u[i].x), "=f"(u[i].y), "=f"(u[i].z), "=f"(u[i].w) : "r"(a + 16 * i) : "memory");
    const float mean = ((u[0].x + u[0].z) + (u[1].x + u[1].z) + (u[2].x + u[2].z)) * (1.f / 6.f);
    const float d0 = u[0].x - mean, d1 = u[0].z - mean, d2 = u[1].x - mean, d3 = u[1].z - mean, d4 = u[2].x - mean, d5 = u[2].z - mean;
    const float var = (((u[0].y + u[0].w) + (u[1].y + u[1].w) + (u[2].y + u[2].w)) +
                       96.f * ((d0 * d0 + d1 * d1) + (d2 * d2 + d3 * d3) + (d4 * d4 + d5 * d5))) * (1.f / 576.f);
    const float vb = __bfloat162float(__float2bfloat16_rn(__bfloat162float(__float2bfloat16_rn(var)) + 1e-5f));
    return make_float2(__bfloat162float(__float2bfloat16_rn(mean)), 1.f / __bfloat162float(__float2bfloat16_rn(sqrtf(vb))));
}
__device__ __forceinline__ uint32_t mbar_test_ballot(uint32_t bars, int idx, int lim) {
    uint32_t m;
    asm volatile("{\n.reg .pred p, q;\n.reg .u32 a;\nsetp.lt.s32 q, %2, %3;\nsetp.ne.u32 p, 0, 0;\nmad.lo.u32 a, %2, 8, %1;\n"
                 "@q mbarrier.test_wait.parity.shared::cta.b64 p, [a], 0;\nvote.sync.ballot.b32 %0, p, 0xffffffff;\n}"
                 : "=r"(m) : "r"(bars), "r"(idx), "r"(lim) : "memory");
    return m;
}
__device__ __forceinline__ void mbar_wait_cl(uint32_t a) {
    uint32_t ok;
    int it = 0;
    do {
        asm volatile("{\n.reg .pred p;\nmbarrier.try_wait.parity.acquire.cluster.shared::cta.b64 p, [%1], 0;\nselp.u32 %0, 1, 0, p;\n}"
                     : "=r"(ok) : "r"(a) : "memory");
        if (++it > SPIN_LIMIT) __trap();
    } while (!ok);
}
__device__ __forceinline__ void tma3(uint32_t dst, const CUtensorMap* m, int c1, int c2, uint32_t bar) {
    asm volatile("cp.async.bulk.tensor.3d.shared::cluster.global.mbarrier::complete_tx::bytes [%0], [%1, {%2, %3, %4}], [%5];"
                 ::"r"(dst), "l"(m), "r"(0), "r"(c1), "r"(c2), "r"(bar) : "memory");
}
__device__ __forceinline__ void tma3_elect(uint32_t dst, const CUtensorMap* m, int c1, int c2, uint32_t bar) {
    asm volatile("{\n.reg .pred p;\nelect.sync _|p, 0xffffffff;\n"
                 "@p cp.async.bulk.tensor.3d.shared::cluster.global.mbarrier::complete_tx::bytes [%0], [%1, {%2, %3, %4}], [%5];\n}"
                 ::"r"(dst), "l"(m), "r"(0), "r"(c1), "r"(c2), "r"(bar) : "memory");
}
__device__ __forceinline__ void ldsm4(uint32_t (&r)[4], uint32_t a) {
    asm volatile("ldmatrix.sync.aligned.m8n8.x4.shared.b16 {%0,%1,%2,%3}, [%4];"
                 : "=r"(r[0]), "=r"(r[1]), "=r"(r[2]), "=r"(r[3]) : "r"(a) : "memory");
}
__device__ __forceinline__ void ldsm4t(uint32_t (&r)[4], uint32_t a) {
    asm volatile("ldmatrix.sync.aligned.m8n8.x4.trans.shared.b16 {%0,%1,%2,%3}, [%4];"
                 : "=r"(r[0]), "=r"(r[1]), "=r"(r[2]), "=r"(r[3]) : "r"(a) : "memory");
}
__device__ __forceinline__ void mma(float (&c)[4], const uint32_t (&a)[4], uint32_t b0, uint32_t b1) {
    asm("mma.sync.aligned.m16n8k16.row.col.f32.bf16.bf16.f32 {%0,%1,%2,%3}, {%4,%5,%6,%7}, {%8,%9}, {%0,%1,%2,%3};"
        : "+f"(c[0]), "+f"(c[1]), "+f"(c[2]), "+f"(c[3])
        : "r"(a[0]), "r"(a[1]), "r"(a[2]), "r"(a[3]), "r"(b0), "r"(b1));
}
__device__ __forceinline__ uint32_t mapa(uint32_t a, uint32_t cta) {
    uint32_t r;
    asm("mapa.shared::cluster.u32 %0, %1, %2;" : "=r"(r) : "r"(a), "r"(cta));
    return r;
}
__device__ __forceinline__ void st_async4(uint32_t rb, int off, int bar, float a, float b, float c, float d) {
    asm volatile("st.async.weak.shared::cluster.mbarrier::complete_tx::bytes.v4.f32 [%0], {%1,%2,%3,%4}, [%5];"
                 ::"r"(rb + off), "f"(a), "f"(b), "f"(c), "f"(d), "r"(rb + BARS + bar * 8) : "memory");
}
__device__ __forceinline__ void st_async2(uint32_t rb, int off, int bar, float a, float b) {
    asm volatile("st.async.weak.shared::cluster.mbarrier::complete_tx::bytes.v2.f32 [%0], {%1,%2}, [%3];"
                 ::"r"(rb + off), "f"(a), "f"(b), "r"(rb + BARS + bar * 8) : "memory");
}
__device__ __forceinline__ void bar_sync(int id, int n) { asm volatile("bar.sync %0, %1;" ::"r"(id), "r"(n) : "memory"); }
__device__ __forceinline__ void bar_arrive(int id, int n) { asm volatile("bar.arrive %0, %1;" ::"r"(id), "r"(n) : "memory"); }
__device__ __forceinline__ void cluster_wait() { asm volatile("barrier.cluster.wait.acquire.aligned;" ::: "memory"); }
__device__ __forceinline__ float4 lds128(uint32_t a) {
    float4 v;
    asm volatile("ld.shared.v4.f32 {%0,%1,%2,%3}, [%4];" : "=f"(v.x), "=f"(v.y), "=f"(v.z), "=f"(v.w) : "r"(a) : "memory");
    return v;
}
__device__ __forceinline__ float2 lds64(uint32_t a) {
    float2 v;
    asm volatile("ld.shared.v2.f32 {%0,%1}, [%2];" : "=f"(v.x), "=f"(v.y) : "r"(a) : "memory");
    return v;
}
__device__ __forceinline__ void sts16(uint32_t a, float v) {
    asm volatile("st.shared.u16 [%0], %1;" ::"r"(a), "h"(__bfloat16_as_ushort(__float2bfloat16_rn(v))) : "memory");
}
__device__ __forceinline__ float bfr(float v) { return __bfloat162float(__float2bfloat16_rn(v)); }
__device__ __forceinline__ float bf_lo(uint32_t w) { return __uint_as_float(w << 16); }
__device__ __forceinline__ float bf_hi(uint32_t w) { return __uint_as_float(w & 0xffff0000u); }
__device__ __forceinline__ uint32_t pack_bf(float lo, float hi) {
    __nv_bfloat162 v = __floats2bfloat162_rn(lo, hi);
    return *reinterpret_cast<uint32_t*>(&v);
}
__device__ __forceinline__ float wsum(float v) {
#pragma unroll
    for (int o = 16; o; o >>= 1) v += __shfl_xor_sync(0xffffffffu, v, o);
    return v;
}
__device__ __forceinline__ float wmax(float v) {
#pragma unroll
    for (int o = 16; o; o >>= 1) v = fmaxf(v, __shfl_xor_sync(0xffffffffu, v, o));
    return v;
}
__device__ __forceinline__ uint32_t sw64(uint32_t a) { return a ^ ((a >> 3) & 0x30u); }
__device__ __forceinline__ uint32_t sw128(uint32_t a) { return a ^ ((a >> 3) & 0x70u); }

__device__ __forceinline__ float lds_bf(uint32_t a) {
    uint16_t v;
    asm volatile("ld.shared.u16 %0, [%1];" : "=h"(v) : "r"(a) : "memory");
    return __uint_as_float((uint32_t)v << 16);
}
__device__ __forceinline__ float4 atom4(float* p, float a, float b, float c) {
    float4 o;
    asm volatile("atom.relaxed.gpu.global.add.v4.f32 {%0,%1,%2,%3}, [%4], {%5,%6,%7,%8};"
                 : "=f"(o.x), "=f"(o.y), "=f"(o.z), "=f"(o.w) : "l"(p), "f"(a), "f"(b), "f"(c), "f"(1.f) : "memory");
    return o;
}
__device__ __forceinline__ void finish(__nv_bfloat16* out, int r, int col, uint32_t epoch, float h0, float h1, float h2,
                                       float f0, float f1, float f2) {
    __nv_bfloat16* po = out + 96 * r + col;
    po[0] = __float2bfloat16_rn(h0 + bfr(f0));
    po[16] = __float2bfloat16_rn(h1 + bfr(f1));
    po[32] = __float2bfloat16_rn(h2 + bfr(f2));
    if (r == 0 && col == 0) g_epoch = epoch + 1;
}
__device__ __forceinline__ float4 sum6(uint32_t a, int stride) {
    float4 v[CL];
#pragma unroll
    for (int s = 0; s < CL; s++) v[s] = lds128(a + s * stride);
    return make_float4(((v[0].x + v[1].x) + (v[2].x + v[3].x)) + (v[4].x + v[5].x), ((v[0].y + v[1].y) + (v[2].y + v[3].y)) + (v[4].y + v[5].y),
                       ((v[0].z + v[1].z) + (v[2].z + v[3].z)) + (v[4].z + v[5].z), ((v[0].w + v[1].w) + (v[2].w + v[3].w)) + (v[4].w + v[5].w));
}
__device__ __forceinline__ float2 sum6h(uint32_t a, int stride) {
    float2 v[CL];
#pragma unroll
    for (int s = 0; s < CL; s++) v[s] = lds64(a + s * stride);
    return make_float2(((v[0].x + v[1].x) + (v[2].x + v[3].x)) + (v[4].x + v[5].x), ((v[0].y + v[1].y) + (v[2].y + v[3].y)) + (v[4].y + v[5].y));
}

template <int I>
__device__ __forceinline__ void produce(uint32_t sb, const CUtensorMap* mk, const CUtensorMap* mv, const CUtensorMap* mo,
                                        const CUtensorMap* m1, const CUtensorMap* m2, int c, int r, int key0, int nk,
                                        int lane, int& mine, int& landed, uint32_t t0) {
    if constexpr (I < NCHUNK) {
        constexpr int narrow = need_landed(I, by_phase(I, NARROW)), wide = need_landed(I, by_phase(I, WIDE));
        const uint32_t bar = sb + BARS + I * 8;
        if constexpr (narrow > 0) {
            int it = 0;
            while (landed < narrow) {
                const uint32_t m = mbar_test_ballot(sb + BARS, mine, I);
                landed += __popc(m);
                mine += ((m >> lane) & 1u) << 5;
                if constexpr (wide < narrow) {
                    uint32_t now;
                    asm volatile("mov.u32 %0, %%globaltimer_lo;" : "=r"(now));
                    if (landed >= wide && (int)(now - t0) >= nominal_ns(I)) break;
                }
                if (++it > 8 * SPIN_LIMIT) __trap();
            }
        }
        if constexpr (I == B_V + WQ_OFF / 8192) mbar_wait(sb + BARS + B_QDONE * 8);
        if constexpr (I == B_WO) mbar_wait(sb + BARS + B_KDONE * 8);
        if constexpr (I == B_W2) mbar_wait(sb + BARS + B_PVDONE * 8);
        if constexpr (I < B_V) {
            if (I - B_K < nk) tma3_elect(sb + R2 + (I - B_K) * 8192, mk, 0, key0 + (I - B_K) * 192, bar);
        } else if constexpr (I < B_WO) {
            if (I - B_V < nk) tma3_elect(sb + R1 + (I - B_V) * 8192, mv, 0, key0 + (I - B_V) * 192, bar);
        } else if constexpr (I < B_W1) {
            tma3_elect(sb + WO_OFF + (I - B_WO) * 6144, mo, 3 * r, 256 * c + (I - B_WO) * 32, bar);
        } else if constexpr (I < B_W2) {
            tma3_elect(sb + W1_OFF + (I - B_W1) * 9216, m1, 9 * c, 96 * r + (I - B_W1) * 16, bar);
        } else {
            tma3_elect(sb + R1 + (I - B_W2) * 6144, m2, 3 * r, 288 * c + (I - B_W2) * 32, bar);
        }
        produce<I + 1>(sb, mk, mv, mo, m1, m2, c, r, key0, nk, lane, mine, landed, t0);
    }
}

__global__ void __cluster_dims__(CL, 1, 1) __launch_bounds__(NTHREADS, 1)
decode_layer_kernel(const __nv_bfloat16* __restrict__ x, const __nv_bfloat16* __restrict__ wq, __nv_bfloat16* __restrict__ out,
                    const __grid_constant__ CUtensorMap mq, const __grid_constant__ CUtensorMap mk, const __grid_constant__ CUtensorMap mv,
                    const __grid_constant__ CUtensorMap mo, const __grid_constant__ CUtensorMap m1,
                    const __grid_constant__ CUtensorMap m2) {
    extern __shared__ __align__(1024) unsigned char smem[];
    const int tid = threadIdx.x, lane = tid & 31;
    const int c = blockIdx.y, r = blockIdx.x;
    if (tid < 384)
        asm volatile("prefetch.global.L2 [%0];" ::"l"(reinterpret_cast<const char*>(wq) + (size_t)(96 * r + (tid >> 2)) * (QD * 2) + c * 512 + (tid & 3) * 128));
    const int warp = __shfl_sync(0xffffffffu, tid >> 5, 0);
    const uint32_t sb = (uint32_t)__cvta_generic_to_shared(smem);
    const int nk = r < 4 ? 11 : 10;
    const int g = lane >> 2, t = lane & 3;

    if (warp == 13) {
        uint32_t t0;
        asm volatile("mov.u32 %0, %%globaltimer_lo;" : "=r"(t0));
        const int key0 = c * SK + (SK - WIN) + 32 * r;
        if (lane == 0) {
            asm volatile("prefetch.tensormap [%0];" ::"l"(&mq) : "memory");
            TLOG1(1);
#pragma unroll
            for (int b = 0; b < B_K; b++) {
                mbar_init(sb + BARS + b * 8, 1);
                mbar_expect(sb + BARS + b * 8, chunk_bytes(b));
            }
            mbar_init(sb + BARS + B_AR * 8, 5);
            asm volatile("fence.mbarrier_init.release.cluster;" ::: "memory");
            TLOG1(2);
#pragma unroll
            for (int i = 0; i < B_K; i++) tma3(sb + WQ_OFF + i * 8192, &mq, 96 * r + i * 16, 4 * c, sb + BARS + i * 8);
            asm volatile("prefetch.tensormap [%0];" ::"l"(&mk) : "memory");
            asm volatile("prefetch.tensormap [%0];" ::"l"(&mv) : "memory");
            asm volatile("prefetch.tensormap [%0];" ::"l"(&mo) : "memory");
            asm volatile("prefetch.tensormap [%0];" ::"l"(&m1) : "memory");
            asm volatile("prefetch.tensormap [%0];" ::"l"(&m2) : "memory");
            TLOG1(3);
        }
        __syncthreads();
        asm volatile("barrier.cluster.arrive.relaxed.aligned;" ::: "memory");
        TLOG(4);
        int mine = lane, landed = 0;
        produce<B_K>(sb, &mk, &mv, &mo, &m1, &m2, c, r, key0, nk, lane, mine, landed, t0);
        __syncwarp();
        TLOG(0);
        cluster_wait();
        TFLUSH();
        return;
    }

    if (warp == 12) {
        const uint32_t* x32 = reinterpret_cast<const uint32_t*>(x);
        uint32_t xr[9];
#pragma unroll
        for (int i = 0; i < 9; i++) xr[i] = __ldg(x32 + lane + 32 * i);
        const uint32_t xs0 = __ldg(x32 + 48 * r + lane), xs1 = __ldg(x32 + 48 * r + 32 + (lane & 15));
        const int col = 48 * (lane >> 4) + (lane & 15);
        const float x0 = __bfloat162float(x[96 * r + col]), x1 = __bfloat162float(x[96 * r + col + 16]), x2 = __bfloat162float(x[96 * r + col + 32]);
        __syncthreads();
        asm volatile("barrier.cluster.arrive.relaxed.aligned;" ::: "memory");
        float s = 0.f;
#pragma unroll
        for (int i = 0; i < 9; i++) s += bf_lo(xr[i]) + bf_hi(xr[i]);
        TLOG(2);
        const float mean = wsum(s) / DM;
        float v = 0.f;
#pragma unroll
        for (int i = 0; i < 9; i++) {
            const float a = bf_lo(xr[i]) - mean, b = bf_hi(xr[i]) - mean;
            v += a * a + b * b;
        }
        const float mb = bfr(mean), sd = bfr(sqrtf(bfr(bfr(wsum(v) / DM) + 1e-5f)));
        asm volatile("st.shared.u32 [%0], %1;" ::"r"(sb + XNV + lane * 4),
                     "r"(pack_bf(bfr(bf_lo(xs0) - mb) / sd, bfr(bf_hi(xs0) - mb) / sd)) : "memory");
        asm volatile("st.shared.u32 [%0], %1;" ::"r"(sb + XNV + 128 + (lane & 15) * 4),
                     "r"(pack_bf(bfr(bf_lo(xs1) - mb) / sd, bfr(bf_hi(xs1) - mb) / sd)) : "memory");
        bar_arrive(1, 288);
        TLOG(0);
        uint32_t epoch;
        asm volatile("ld.global.u32 %0, [%1];" : "=r"(epoch) : "l"(&g_epoch) : "memory");
        const uint32_t par = epoch & 1u;
        if (c == 0) {
            *reinterpret_cast<float4*>(&g_acc[par ^ 1][0][r][lane * 4]) = make_float4(0.f, 0.f, 0.f, 0.f);
            *reinterpret_cast<float4*>(&g_acc[par ^ 1][1][r][lane * 4]) = make_float4(0.f, 0.f, 0.f, 0.f);
        }
        cluster_wait();
        mbar_wait(sb + BARS + B_B * 8);
        float a0, a1, a2, n;
        int it = 0;
        do {
            asm volatile("ld.relaxed.gpu.global.v4.f32 {%0,%1,%2,%3}, [%4];" : "=f"(a0), "=f"(a1), "=f"(a2), "=f"(n) : "l"(&g_acc[par][0][r][lane * 4]) : "memory");
            if (++it > SPIN_LIMIT) __trap();
        } while (n != N_ATT);
        const float h0 = bfr(x0 + bfr(a0)), h1 = bfr(x1 + bfr(a1)), h2 = bfr(x2 + bfr(a2));
        sts16(sb + HV + col * 2, h0); sts16(sb + HV + col * 2 + 32, h1); sts16(sb + HV + col * 2 + 64, h2);
        __syncwarp();
        if (lane == 0) mbar_arrive(sb + BARS + B_H * 8);
        TLOG(9);
        const float ctr = __shfl_sync(0xffffffffu, h0, 0);
        const float d0 = h0 - ctr, d1 = h1 - ctr, d2 = h2 - ctr;
        float s1 = d0 + d1 + d2, s2 = d0 * d0 + d1 * d1 + d2 * d2;
#pragma unroll
        for (int o = 16; o; o >>= 1) {
            s1 += __shfl_xor_sync(0xffffffffu, s1, o);
            s2 += __shfl_xor_sync(0xffffffffu, s2, o);
        }
        if (lane < CL) st_async2(mapa(sb, lane), INST + r * 8, B_ST, ctr + s1 * (1.f / 96.f), s2 - s1 * s1 * (1.f / 96.f));
        TLOG(10);
        if (c == 3) {
            const float4 o = atom4(&g_acc[par][1][r][lane * 4], h0, h1, h2);
            if (o.w == N_OUT - 1.f) finish(out, r, col, epoch, h0, h1, h2, o.x, o.y, o.z);
        }
        TFLUSH();
        return;
    }

    if (warp < 11) {
        const int b0 = B_K + 5 * warp;
        if (lane == 0) {
#pragma unroll
            for (int i = 0; i < 5; i++) {
                const int b = b0 + i;
                mbar_init(sb + BARS + b * 8, b == B_KDONE ? 11 : (b == B_QDONE || b == B_PVDONE) ? 8 : 1);
            }
        }
        __syncwarp();
        const int b = b0 + lane;
        if (lane < 5 && b < B_QDONE) {
            const uint32_t bytes = b < NCHUNK ? chunk_bytes(b) : b == B_ML ? 1056 : b == B_ST ? 48 : (b == B_A || b == B_B) ? 6144 : 6912;
            mbar_expect(sb + BARS + b * 8, (nk == 10 && (b == B_K + 10 || b == B_V + 10)) ? 0 : bytes);
        }
        asm volatile("fence.mbarrier_init.release.cluster;" ::: "memory");
    }
    __syncthreads();
    asm volatile("barrier.cluster.arrive.relaxed.aligned;" ::: "memory");
    TLOG(7);
    uint32_t epoch = 0;
    if (warp < 6) asm volatile("ld.global.u32 %0, [%1];" : "=r"(epoch) : "l"(&g_epoch) : "memory");
    const uint32_t rb0 = mapa(sb, t), rb1 = mapa(sb, 4 + (t & 1));
    const int trow = (lane & 7) + 8 * (lane >> 4), tcol = (lane >> 3) & 1;

    if (warp < 8) {
        bar_sync(1, 288);
        uint32_t b[3][4];
#pragma unroll
        for (int u = 0; u < 3; u++) ldsm4(b[u], sb + XNV + u * 64 + (lane >> 3) * 16);
        float acc[2][4] = {};
#pragma unroll
        for (int s = 0; s < 6; s++) {
            mbar_wait(sb + BARS + (B_WQ + s) * 8);
#pragma unroll
            for (int n = 0; n < 2; n++) {
                uint32_t a[4];
                ldsm4t(a, sb + WQ_OFF + s * 8192 + (warp >> 1) * 2048 + sw128(trow * 128 + (4 * (warp & 1) + 2 * n + tcol) * 16));
                mma(acc[n], a, b[s >> 1][(s & 1) * 2], b[s >> 1][(s & 1) * 2 + 1]);
            }
        }
        TLOG(0);
        cluster_wait();
        const int off = INA + r * 1024 + (warp * 8 + g) * 16;
        st_async4(rb0, off, B_A, acc[0][0], acc[0][2], acc[1][0], acc[1][2]);
        if (t < 2) st_async4(rb1, off, B_A, acc[0][0], acc[0][2], acc[1][0], acc[1][2]);
        if (lane == 0) mbar_arrive(sb + BARS + B_QDONE * 8);
    } else {
        cluster_wait();
        if (warp < 10) {
            const int i = tid - 256;
            mbar_wait_cl(sb + BARS + B_A * 8);
            const float4 v = sum6(sb + INA + i * 16, 1024);
            const int n = 32 * (i >> 3) + (i & 7);
            const uint32_t a = sb + QV + (n >> 7) * 272 + (n & 127) * 2;
            sts16(a, v.x); sts16(a + 16, v.y); sts16(a + 32, v.z); sts16(a + 48, v.w);
        }
    }

    if (warp < 11) {
        bar_sync(2, 352);
        TLOG(1);
        float s0 = -INFINITY, s1 = -INFINITY, m0 = -INFINITY, m1v = -INFINITY, e0 = 0.f, e1 = 0.f, l0 = 0.f, l1 = 0.f;
        if (warp < nk) {
            uint32_t b[4][4];
#pragma unroll
            for (int u = 0; u < 4; u++) ldsm4(b[u], sb + QV + (lane & 1) * 272 + (4 * u + (lane >> 3)) * 16);
            float acc[2][4] = {};
            mbar_wait(sb + BARS + (B_K + warp) * 8);
            TLOG(2);
            const uint32_t krow = ((lane & 7) + 8 * ((lane >> 3) & 1)) * 256 + (lane >> 4) * 16;
#pragma unroll
            for (int s = 0; s < 8; s++) {
#pragma unroll
                for (int n = 0; n < 2; n++) {
                    uint32_t a[4];
                    ldsm4(a, sb + R2 + warp * 8192 + sw128(krow + n * 4096 + s * 32));
                    mma(acc[n], a, b[s >> 1][(s & 1) * 2], b[s >> 1][(s & 1) * 2 + 1]);
                }
            }
            const float r0 = t == 0 ? acc[0][0] : t == 1 ? acc[0][2] : t == 2 ? acc[1][0] : acc[1][2];
            const float r1 = t == 0 ? acc[0][1] : t == 1 ? acc[0][3] : t == 2 ? acc[1][1] : acc[1][3];
            s0 = bfr(bfr(r0) * 0.08838834764831845f);
            s1 = bfr(bfr(r1) * 0.08838834764831845f);
            m0 = wmax(s0); m1v = wmax(s1);
            e0 = __expf(s0 - m0); e1 = __expf(s1 - m1v);
            l0 = wsum(e0); l1 = wsum(e1);
        }
        if (lane == 0) mbar_arrive(sb + BARS + B_KDONE * 8);
        if (lane < CL) st_async4(mapa(sb, lane), INML + (r * 11 + warp) * 16, B_ML, m0, m1v, l0, l1);
        mbar_wait_cl(sb + BARS + B_ML * 8);
        if (warp < nk) {
            const float4 u0 = lds128(sb + INML + lane * 16), u1 = lds128(sb + INML + (lane + 32) * 16);
            float4 u2 = make_float4(-INFINITY, -INFINITY, 0.f, 0.f);
            if (lane < 2) u2 = lds128(sb + INML + (lane + 64) * 16);
            const float M0 = wmax(fmaxf(fmaxf(u0.x, u1.x), u2.x)), M1 = wmax(fmaxf(fmaxf(u0.y, u1.y), u2.y));
            const float L0 = wsum(u0.z * __expf(u0.x - M0) + u1.z * __expf(u1.x - M0) + u2.z * __expf(u2.x - M0));
            const float L1 = wsum(u0.w * __expf(u0.y - M1) + u1.w * __expf(u1.y - M1) + u2.w * __expf(u2.y - M1));
            const uint32_t a = sb + PVV + (32 * warp + 8 * t + g) * 2;
            sts16(a, e0 * (__expf(m0 - M0) / L0));
            sts16(a + 704, e1 * (__expf(m1v - M1) / L1));
        }
        TLOG(3);
    }

    if (warp < 8) {
        bar_sync(3, 352);
        float acc[2][4] = {};
        const uint32_t vrow = trow * 256 + (2 * warp + tcol) * 16;
#pragma unroll
        for (int j = 0; j < 11; j++) {
            if (j < nk) {
                uint32_t b[4], a0[4], a1[4];
                ldsm4(b, sb + PVV + (lane & 1) * 704 + j * 64 + (lane >> 3) * 16);
                mbar_wait(sb + BARS + (B_V + j) * 8);
                ldsm4t(a0, sb + R1 + j * 8192 + sw128(vrow));
                ldsm4t(a1, sb + R1 + j * 8192 + 4096 + sw128(vrow));
                mma(acc[0], a0, b[0], b[1]);
                mma(acc[1], a1, b[2], b[3]);
            }
        }
        const float v0 = acc[0][0] + acc[1][0], v1 = acc[0][1] + acc[1][1], v2 = acc[0][2] + acc[1][2], v3 = acc[0][3] + acc[1][3];
        const int off = INB + r * 1024 + (warp * 8 + g) * 16;
        st_async4(rb0, off, B_B, v0, v1, v2, v3);
        if (t < 2) st_async4(rb1, off, B_B, v0, v1, v2, v3);
        if (lane == 0) mbar_arrive(sb + BARS + B_PVDONE * 8);
        TLOG(4);
    } else if (warp < 11) {
        bar_arrive(3, 352);
        if (warp < 10) {
            const int i = tid - 256;
            mbar_wait_cl(sb + BARS + B_B * 8);
            const float4 v = sum6(sb + INB + i * 16, 1024);
            const uint32_t a = sb + OV + (16 * (i >> 3) + (i & 7)) * 2;
            sts16(a, v.x); sts16(a + 256, v.y); sts16(a + 16, v.z); sts16(a + 272, v.w);
            bar_arrive(4, 256);
            TLOG(5);
        }
    }

    if (warp < 6) {
        const int half = warp & 1, kg = warp >> 1;
        const uint32_t wrow = trow * 192 + (6 * half + tcol) * 16;
        const uint32_t wa[3] = {sw64(wrow), sw64(wrow + 32), sw64(wrow + 64)};
        float* accC = &g_acc[epoch & 1u][0][r][(half * 16 + (t & 1) * 8 + g) * 4];
        {
            bar_sync(4, 256);
            TLOG(5);
            float acc[3][2][4] = {};
#pragma unroll
            for (int i = 0; i < 3; i++) {
                const int j = kg + 3 * i;
                if (j < 8) {
                    uint32_t b[4];
                    ldsm4(b, sb + OV + j * 64 + (lane >> 3) * 16);
                    mbar_wait(sb + BARS + (B_WO + j) * 8);
#pragma unroll
                    for (int n = 0; n < 3; n++) {
                        uint32_t a0[4], a1[4];
                        ldsm4t(a0, sb + WO_OFF + j * 6144 + wa[n]);
                        ldsm4t(a1, sb + WO_OFF + j * 6144 + 3072 + wa[n]);
                        mma(acc[n][0], a0, b[0], b[1]);
                        mma(acc[n][1], a1, b[2], b[3]);
                    }
                }
            }
            float v[3];
#pragma unroll
            for (int n = 0; n < 3; n++) v[n] = t == 0 ? acc[n][0][0] + acc[n][1][0] : acc[n][0][2] + acc[n][1][2];
            if (t < 2)
                asm volatile("red.relaxed.gpu.global.add.v4.f32 [%0], {%1,%2,%3,%4};" ::"l"(accC), "f"(v[0]), "f"(v[1]), "f"(v[2]), "f"(1.f) : "memory");
            TLOG(6);
        }
        uint32_t a[2][3][2][4], b[3][4];
#pragma unroll
        for (int i = 0; i < 2; i++) {
            const int j = kg + 3 * i;
            mbar_wait(sb + BARS + (B_W2 + j) * 8);
#pragma unroll
            for (int n = 0; n < 3; n++) {
                ldsm4t(a[i][n][0], sb + R1 + j * 6144 + wa[n]);
                ldsm4t(a[i][n][1], sb + R1 + j * 6144 + 3072 + wa[n]);
            }
        }
        TLOG(11);
        mbar_wait(sb + BARS + B_AR * 8);
        TLOG(12);
#pragma unroll
        for (int i = 0; i < 3; i++) ldsm4(b[i], sb + AV + (kg + 3 * i) * 64 + (lane >> 3) * 16);
        const int col = 48 * half + 8 * (t & 1) + g;
        const float h0 = lds_bf(sb + HV + col * 2), h1 = lds_bf(sb + HV + col * 2 + 32), h2 = lds_bf(sb + HV + col * 2 + 64);
        float acc[3][2][4] = {};
#pragma unroll
        for (int i = 0; i < 2; i++)
#pragma unroll
            for (int n = 0; n < 3; n++) {
                mma(acc[n][0], a[i][n][0], b[i][0], b[i][1]);
                mma(acc[n][1], a[i][n][1], b[i][2], b[i][3]);
            }
        mbar_spin(sb + BARS + (B_W2 + kg + 6) * 8);
#pragma unroll
        for (int n = 0; n < 3; n++) {
            ldsm4t(a[0][n][0], sb + R1 + (kg + 6) * 6144 + wa[n]);
            ldsm4t(a[0][n][1], sb + R1 + (kg + 6) * 6144 + 3072 + wa[n]);
        }
#pragma unroll
        for (int n = 0; n < 3; n++) {
            mma(acc[n][0], a[0][n][0], b[2][0], b[2][1]);
            mma(acc[n][1], a[0][n][1], b[2][2], b[2][3]);
        }
        TLOG(13);
        if (t < 2) {
            float v[3];
#pragma unroll
            for (int n = 0; n < 3; n++) v[n] = t == 0 ? acc[n][0][0] + acc[n][1][0] : acc[n][0][2] + acc[n][1][2];
            const float4 o = atom4(accC + CL * 128, v[0], v[1], v[2]);
            if (o.w == N_OUT - 1.f) finish(out, r, col, epoch, h0, h1, h2, (o.x + v[0]) - h0, (o.y + v[1]) - h1, (o.z + v[2]) - h2);
        }
        __syncwarp();
        TLOG(8);
    } else {
        {
            const int w = warp - 6;
            uint32_t a[3][6][4];
            float cs[3][4] = {}, p[3][2][4] = {};
            const uint32_t arow = trow * 576 + (6 * w + tcol) * 16;
            auto send = [&](int box, int bar, float v0, float v1, float v2, float v3, float v4, float v5) {
                const int off4 = box + r * 1152 + (w * 8 + g) * 16, off2 = box + r * 1152 + 768 + (w * 8 + g) * 8;
                st_async4(rb0, off4, bar, v0, v1, v2, v3);
                st_async2(rb0, off2, bar, v4, v5);
                if (t < 2) {
                    st_async4(rb1, off4, bar, v0, v1, v2, v3);
                    st_async2(rb1, off2, bar, v4, v5);
                }
            };
#pragma unroll
            for (int s = 0; s < 6; s++) {
                mbar_wait(sb + BARS + (B_W1 + s) * 8);
#pragma unroll
                for (int n = 0; n < 3; n++) {
                    ldsm4t(a[n][s], sb + W1_OFF + s * 9216 + sw64(arow + n * 32));
                    mma(cs[n], a[n][s], 0x3f803f80u, 0x3f803f80u);
                }
            }
            send(INP2, B_P2, cs[0][0], cs[0][2], cs[1][0], cs[1][2], cs[2][0], cs[2][2]);
            TLOG(8);
            mbar_wait(sb + BARS + B_H * 8);
            TLOG(9);
#pragma unroll
            for (int u = 0; u < 3; u++) {
                uint32_t b[4];
                ldsm4(b, sb + HV + u * 64 + (lane >> 3) * 16);
#pragma unroll
                for (int n = 0; n < 3; n++) {
                    mma(p[n][0], a[n][2 * u], b[0], b[1]);
                    mma(p[n][1], a[n][2 * u + 1], b[2], b[3]);
                }
            }
            send(INP1, B_P1, p[0][0][0] + p[0][1][0], p[0][0][2] + p[0][1][2], p[1][0][0] + p[1][1][0], p[1][0][2] + p[1][1][2],
                 p[2][0][0] + p[2][1][0], p[2][0][2] + p[2][1][2]);
            TLOG(10);
        }
        if (warp < 11) {
            const int i = min(tid - 192, 143);
            mbar_wait_cl(sb + BARS + B_P2 * 8);
            const float2 cs = sum6h(sb + INP2 + i * 8, 1152);
            mbar_wait_cl(sb + BARS + B_ST * 8);
            const float2 st = ln_stats(sb + INST);
            const float mb = st.x, rs = st.y;
            mbar_wait_cl(sb + BARS + B_P1 * 8);
            TLOG(11);
            const float2 p = sum6h(sb + INP1 + i * 8, 1152);
            const float y0 = bfr((p.x - mb * cs.x) * rs), y1 = bfr((p.y - mb * cs.y) * rs);
            const uint32_t a = sb + AV + (i < 96 ? 48 * (i >> 4) + 16 * (i & 1) + ((i >> 1) & 7) : 48 * ((i - 96) >> 3) + 32 + (i & 7)) * 2;
            sts16(a, __fdividef(y0, 1.f + __expf(-y0)));
            sts16(a + 16, __fdividef(y1, 1.f + __expf(-y1)));
            __syncwarp();
            if (lane == 0) mbar_arrive(sb + BARS + B_AR * 8);
            TLOG(12);
        }
    }
    TFLUSH();
}

__device__ float f_q[QD], f_o[QD], f_h[DM], f_a[FF];

__device__ __forceinline__ float block_sum(float v, float* red) {
    v = wsum(v);
    __syncthreads();
    if ((threadIdx.x & 31) == 0) red[threadIdx.x >> 5] = v;
    __syncthreads();
    float s = 0.f;
    for (int i = 0; i < (int)(blockDim.x >> 5); i++) s += red[i];
    return s;
}
__device__ void fb_ln(const __nv_bfloat16* xb, const float* xf, float* xn, float* red) {
    float s = 0.f;
    for (int i = threadIdx.x; i < DM; i += blockDim.x) { xn[i] = xb ? __bfloat162float(xb[i]) : xf[i]; s += xn[i]; }
    const float mean = block_sum(s, red) / DM;
    float v = 0.f;
    for (int i = threadIdx.x; i < DM; i += blockDim.x) v += (xn[i] - mean) * (xn[i] - mean);
    const float sd = bfr(sqrtf(bfr(bfr(block_sum(v, red) / DM) + 1e-5f))), mb = bfr(mean);
    for (int i = threadIdx.x; i < DM; i += blockDim.x) xn[i] = bfr(bfr(xn[i] - mb) / sd);
    __syncthreads();
}
__global__ void fb_ln_gemv(const __nv_bfloat16* x, const __nv_bfloat16* w, int n, int mode) {
    __shared__ float xn[DM], red[8];
    fb_ln(mode == 0 ? x : nullptr, f_h, xn, red);
    const int j = blockIdx.x * blockDim.x + threadIdx.x;
    float s = 0.f;
    for (int k = 0; k < DM; k++) s += xn[k] * __bfloat162float(w[(size_t)k * n + j]);
    s = bfr(s);
    if (mode == 0) f_q[j] = s; else f_a[j] = bfr(s / (1.f + __expf(-s)));
}
__global__ void fb_attn(const __nv_bfloat16* kc, const __nv_bfloat16* vc) {
    __shared__ float p[WIN], red[8];
    const int h = blockIdx.x;
    const size_t base = ((size_t)(h >> 1) * SK + (SK - WIN)) * DH;
    float mx = -INFINITY;
    for (int k = threadIdx.x; k < WIN; k += blockDim.x) {
        float s = 0.f;
        for (int d = 0; d < DH; d++) s += f_q[h * DH + d] * __bfloat162float(kc[base + (size_t)k * DH + d]);
        p[k] = bfr(bfr(s) * 0.08838834764831845f);
        mx = fmaxf(mx, p[k]);
    }
    mx = wmax(mx);
    if ((threadIdx.x & 31) == 0) red[threadIdx.x >> 5] = mx;
    __syncthreads();
    for (int i = 0; i < (int)(blockDim.x >> 5); i++) mx = fmaxf(mx, red[i]);
    float l = 0.f;
    for (int k = threadIdx.x; k < WIN; k += blockDim.x) { p[k] = __expf(p[k] - mx); l += p[k]; }
    l = block_sum(l, red);
    float o = 0.f;
    for (int k = 0; k < WIN; k++) o += bfr(p[k] / l) * __bfloat162float(vc[base + (size_t)k * DH + threadIdx.x]);
    f_o[h * DH + threadIdx.x] = bfr(o);
}
__global__ void fb_out_gemv(const __nv_bfloat16* x, const __nv_bfloat16* w, int rows, int mode, __nv_bfloat16* out) {
    __shared__ float red[8][32];
    const int j = blockIdx.x * 32 + (threadIdx.x & 31);
    const float* v = mode == 0 ? f_o : f_a;
    float s = 0.f;
    for (int k = threadIdx.x >> 5; k < rows; k += 8) s += v[k] * __bfloat162float(w[(size_t)k * DM + j]);
    red[threadIdx.x >> 5][threadIdx.x & 31] = s;
    __syncthreads();
    if (threadIdx.x < 32) {
        s = 0.f;
        for (int i = 0; i < 8; i++) s += red[i][threadIdx.x];
        if (mode == 0) f_h[j] = bfr(__bfloat162float(x[j]) + bfr(s)); else out[j] = __float2bfloat16_rn(f_h[j] + bfr(s));
    }
}

typedef CUresult (*EncodeFn)(CUtensorMap*, CUtensorMapDataType, cuuint32_t, void*, const cuuint64_t*, const cuuint64_t*,
                             const cuuint32_t*, const cuuint32_t*, CUtensorMapInterleave, CUtensorMapSwizzle,
                             CUtensorMapL2promotion, CUtensorMapFloatOOBfill);

bool make_map(EncodeFn enc, CUtensorMap* m, const void* p, int rows, int cols, int inner, int groups, int boxrows,
              bool rows_first = false) {
    const int a = rows_first ? 2 : 1, b = 3 - a;
    cuuint64_t dim[3], str[3];
    cuuint32_t box[3];
    dim[0] = inner; dim[a] = cols / inner; dim[b] = rows;
    str[a - 1] = inner * 2; str[b - 1] = cols * 2;
    box[0] = inner; box[a] = groups; box[b] = boxrows;
    const cuuint32_t es[3] = {1, 1, 1};
    return enc(m, CU_TENSOR_MAP_DATA_TYPE_BFLOAT16, 3, const_cast<void*>(p), dim, str, box, es, CU_TENSOR_MAP_INTERLEAVE_NONE,
               inner == 64 ? CU_TENSOR_MAP_SWIZZLE_128B : CU_TENSOR_MAP_SWIZZLE_64B, CU_TENSOR_MAP_L2_PROMOTION_NONE,
               CU_TENSOR_MAP_FLOAT_OOB_FILL_NONE) == CUDA_SUCCESS;
}

}

extern "C" void kernel_launch(void* const* d_in, const int* in_sizes, int n_in, void* d_out, int out_size) {
    const __nv_bfloat16* x = (const __nv_bfloat16*)d_in[0];
    const __nv_bfloat16* kc = (const __nv_bfloat16*)d_in[1];
    const __nv_bfloat16* vc = (const __nv_bfloat16*)d_in[2];
    const __nv_bfloat16* wq = (const __nv_bfloat16*)d_in[3];
    const __nv_bfloat16* wo = (const __nv_bfloat16*)d_in[4];
    const __nv_bfloat16* w1 = (const __nv_bfloat16*)d_in[6];
    const __nv_bfloat16* w2 = (const __nv_bfloat16*)d_in[7];
    __nv_bfloat16* out = (__nv_bfloat16*)d_out;
    cudaStream_t stream = cudaStreamPerThread;

    static int state = 0;
    static EncodeFn enc = nullptr;
    if (state == 0) {
        state = 2;
        void* fn = nullptr;
        cudaDriverEntryPointQueryResult qr;
        if (cudaGetDriverEntryPoint("cuTensorMapEncodeTiled", &fn, cudaEnableDefault, &qr) == cudaSuccess &&
            qr == cudaDriverEntryPointSuccess && fn &&
            cudaFuncSetAttribute(decode_layer_kernel, cudaFuncAttributeMaxDynamicSharedMemorySize, SMEM_BYTES) == cudaSuccess) {
            enc = (EncodeFn)fn;
            cudaLaunchConfig_t cfg = {};
            cfg.gridDim = dim3(CL, HKV); cfg.blockDim = dim3(NTHREADS); cfg.dynamicSmemBytes = SMEM_BYTES;
            cudaLaunchAttribute at[1];
            at[0].id = cudaLaunchAttributeClusterDimension;
            at[0].val.clusterDim.x = CL; at[0].val.clusterDim.y = 1; at[0].val.clusterDim.z = 1;
            cfg.attrs = at; cfg.numAttrs = 1;
            int nc = 0;
            if (cudaOccupancyMaxActiveClusters(&nc, decode_layer_kernel, &cfg) == cudaSuccess && nc >= HKV) state = 1;
        }
        (void)cudaGetLastError();
    }
    CUtensorMap mq, mk, mv, mo, m1, m2;
    if (state == 1 && make_map(enc, &mq, wq, DM, QD, 64, 4, 16, true) && make_map(enc, &mk, kc, HKV * SK, DH, 64, 2, 32) && make_map(enc, &mv, vc, HKV * SK, DH, 64, 2, 32) &&
        make_map(enc, &mo, wo, QD, DM, 32, 3, 32) && make_map(enc, &m1, w1, DM, FF, 32, 9, 16) &&
        make_map(enc, &m2, w2, FF, DM, 32, 3, 32)) {
        decode_layer_kernel<<<dim3(CL, HKV), NTHREADS, SMEM_BYTES, stream>>>(x, wq, out, mq, mk, mv, mo, m1, m2);
        return;
    }
    fb_ln_gemv<<<QD / 128, 128, 0, stream>>>(x, wq, QD, 0);
    fb_attn<<<2 * HKV, 128, 0, stream>>>(kc, vc);
    fb_out_gemv<<<DM / 32, 256, 0, stream>>>(x, wo, QD, 0, out);
    fb_ln_gemv<<<FF / 128, 128, 0, stream>>>(x, w1, FF, 1);
    fb_out_gemv<<<DM / 32, 256, 0, stream>>>(x, w2, FF, 1, out);
}
```

```cpp
#include <cuda_runtime.h>
#include <cuda_bf16.h>
#include <cuda.h>
#include <stdint.h>

namespace {

constexpr int DM = 576, HKV = 16, SK = 8192, WIN = 2048, DH = 128, FF = 4608, QD = 4096;
constexpr int CL = 6;
constexpr int NWARPS = 14;
constexpr int NTHREADS = NWARPS * 32;

constexpr int R1 = 0;
constexpr int WQ_OFF = 90112 - 6 * 8192;
constexpr int R2 = 90112;
constexpr int WO_OFF = R2;
constexpr int W1_OFF = R2 + 49152;
constexpr int INA = R2 + 104448;
constexpr int INB = INA + 6144;
constexpr int INP2 = INB + 6144;
constexpr int INP1 = INP2 + 6912;
constexpr int INML = INP1 + 6912;
constexpr int INST = INML + 1088;
constexpr int XNV = INST + 64;
constexpr int QV = XNV + 192;
constexpr int PVV = QV + 544;
constexpr int OV = PVV + 1408;
constexpr int HV = OV + 512;
constexpr int AV = HV + 192;
constexpr int BARS = AV + 576;
constexpr int SMEM_BYTES = BARS + 64 * 8;
static_assert(SMEM_BYTES <= 232448 - 2048, "smem");

constexpr int B_WQ = 0, B_K = 6, B_V = 17, B_WO = 28, B_W1 = 36, B_W2 = 42, NCHUNK = 51;
constexpr int B_A = 51, B_ML = 52, B_B = 53, B_P2 = 54, B_ST = 55, B_P1 = 56;
constexpr int B_QDONE = 57, B_KDONE = 58, B_PVDONE = 59, B_H = 60, B_AR = 61, NBAR = 62;

__host__ __device__ constexpr int chunk_bytes(int i) {
    return i < B_WO ? 8192 : i < B_W1 ? 6144 : i < B_W2 ? 9216 : 6144;
}
#define NARROW 6440383836LL
#define WIDE 6464645644LL
#define PACE_PS 478
#define PACE_T0 600
__host__ __device__ constexpr int by_phase(int i, long long w) {
    return 1024 * (int)(w / (i < B_V ? 100000000 : i < B_WO ? 1000000 : i < B_W1 ? 10000 : i < B_W2 ? 100 : 1) % 100);
}
__host__ __device__ constexpr int need_landed(int i, int w) {
    int s = 0, j = i;
    while (j >= 0 && s + chunk_bytes(j) <= w) { s += chunk_bytes(j); j--; }
    return j + 1;
}
__host__ __device__ constexpr int nominal_ns(int i) {
    int cum = -44 * 1024 - (i >= B_V ? 2731 : 0) - (i >= B_WO ? 2731 : 0);
    for (int j = 0; j <= i; j++) cum += chunk_bytes(j);
    return PACE_T0 + cum / 16 * PACE_PS / 1000;
}

constexpr float N_ATT = 48.f;
constexpr float N_OUT = 49.f;
__device__ __align__(1024) float g_acc[2][2][CL][128];
__device__ uint32_t g_epoch;

#define TLOG(i) do {} while (0)
#define TFLUSH() do {} while (0)
#define TLOG1(i) do {} while (0)

__device__ __forceinline__ void mbar_init(uint32_t a, uint32_t c) {
    asm volatile("mbarrier.init.shared::cta.b64 [%0], %1;" ::"r"(a), "r"(c) : "memory");
}
__device__ __forceinline__ void mbar_expect(uint32_t a, uint32_t b) {
    asm volatile("mbarrier.arrive.expect_tx.shared::cta.b64 _, [%0], %1;" ::"r"(a), "r"(b) : "memory");
}
__device__ __forceinline__ void mbar_arrive(uint32_t a) {
    asm volatile("mbarrier.arrive.shared::cta.b64 _, [%0];" ::"r"(a) : "memory");
}
constexpr int SPIN_LIMIT = 1 << 21;
__device__ __forceinline__ void mbar_wait(uint32_t a) {
    uint32_t ok;
    int it = 0;
    do {
        asm volatile("{\n.reg .pred p;\nmbarrier.try_wait.parity.shared::cta.b64 p, [%1], 0;\nselp.u32 %0, 1, 0, p;\n}"
                     : "=r"(ok) : "r"(a) : "memory");
        if (++it > SPIN_LIMIT) __trap();
    } while (!ok);
}
__device__ __forceinline__ void mbar_spin(uint32_t a) {
    uint32_t ok;
    int it = 0;
    do {
        asm volatile("{\n.reg .pred p;\nmbarrier.test_wait.parity.shared::cta.b64 p, [%1], 0;\nselp.u32 %0, 1, 0, p;\n}"
                     : "=r"(ok) : "r"(a) : "memory");
        if (++it > 8 * SPIN_LIMIT) __trap();
    } while (!ok);
}
__device__ __forceinline__ float2 ln_stats(uint32_t a) {
    float4 u[3];
#pragma unroll
    for (int i = 0; i < 3; i++)
        asm volatile("ld.shared.v4.f32 {%0,%1,%2,%3}, [%4];" : "=f"(u[i].x), "=f"(u[i].y), "=f"(u[i].z), "=f"(u[i].w) : "r"(a + 16 * i) : "memory");
    const float mean = ((u[0].x + u[0].z) + (u[1].x + u[1].z) + (u[2].x + u[2].z)) * (1.f / 6.f);
    const float d0 = u[0].x - mean, d1 = u[0].z - mean, d2 = u[1].x - mean, d3 = u[1].z - mean, d4 = u[2].x - mean, d5 = u[2].z - mean;
    const float var = (((u[0].y + u[0].w) + (u[1].y + u[1].w) + (u[2].y + u[2].w)) +
                       96.f * ((d0 * d0 + d1 * d1) + (d2 * d2 + d3 * d3) + (d4 * d4 + d5 * d5))) * (1.f / 576.f);
    const float vb = __bfloat162float(__float2bfloat16_rn(__bfloat162float(__float2bfloat16_rn(var)) + 1e-5f));
    return make_float2(__bfloat162float(__float2bfloat16_rn(mean)), 1.f / __bfloat162float(__float2bfloat16_rn(sqrtf(vb))));
}
__device__ __forceinline__ uint32_t mbar_test_ballot(uint32_t bars, int idx, int lim) {
    uint32_t m;
    asm volatile("{\n.reg .pred p, q;\n.reg .u32 a;\nsetp.lt.s32 q, %2, %3;\nsetp.ne.u32 p, 0, 0;\nmad.lo.u32 a, %2, 8, %1;\n"
                 "@q mbarrier.test_wait.parity.shared::cta.b64 p, [a], 0;\nvote.sync.ballot.b32 %0, p, 0xffffffff;\n}"
                 : "=r"(m) : "r"(bars), "r"(idx), "r"(lim) : "memory");
    return m;
}
__device__ __forceinline__ void mbar_wait_cl(uint32_t a) {
    uint32_t ok;
    int it = 0;
    do {
        asm volatile("{\n.reg .pred p;\nmbarrier.try_wait.parity.acquire.cluster.shared::cta.b64 p, [%1], 0;\nselp.u32 %0, 1, 0, p;\n}"
                     : "=r"(ok) : "r"(a) : "memory");
        if (++it > SPIN_LIMIT) __trap();
    } while (!ok);
}
__device__ __forceinline__ void tma3(uint32_t dst, const CUtensorMap* m, int c1, int c2, uint32_t bar) {
    asm volatile("cp.async.bulk.tensor.3d.shared::cluster.global.mbarrier::complete_tx::bytes [%0], [%1, {%2, %3, %4}], [%5];"
                 ::"r"(dst), "l"(m), "r"(0), "r"(c1), "r"(c2), "r"(bar) : "memory");
}
__device__ __forceinline__ void tma3_elect(uint32_t dst, const CUtensorMap* m, int c1, int c2, uint32_t bar) {
    asm volatile("{\n.reg .pred p;\nelect.sync _|p, 0xffffffff;\n"
                 "@p cp.async.bulk.tensor.3d.shared::cluster.global.mbarrier::complete_tx::bytes [%0], [%1, {%2, %3, %4}], [%5];\n}"
                 ::"r"(dst), "l"(m), "r"(0), "r"(c1), "r"(c2), "r"(bar) : "memory");
}
__device__ __forceinline__ void ldsm4(uint32_t (&r)[4], uint32_t a) {
    asm volatile("ldmatrix.sync.aligned.m8n8.x4.shared.b16 {%0,%1,%2,%3}, [%4];"
                 : "=r"(r[0]), "=r"(r[1]), "=r"(r[2]), "=r"(r[3]) : "r"(a) : "memory");
}
__device__ __forceinline__ void ldsm4t(uint32_t (&r)[4], uint32_t a) {
    asm volatile("ldmatrix.sync.aligned.m8n8.x4.trans.shared.b16 {%0,%1,%2,%3}, [%4];"
                 : "=r"(r[0]), "=r"(r[1]), "=r"(r[2]), "=r"(r[3]) : "r"(a) : "memory");
}
__device__ __forceinline__ void mma(float (&c)[4], const uint32_t (&a)[4], uint32_t b0, uint32_t b1) {
    asm("mma.sync.aligned.m16n8k16.row.col.f32.bf16.bf16.f32 {%0,%1,%2,%3}, {%4,%5,%6,%7}, {%8,%9}, {%0,%1,%2,%3};"
        : "+f"(c[0]), "+f"(c[1]), "+f"(c[2]), "+f"(c[3])
        : "r"(a[0]), "r"(a[1]), "r"(a[2]), "r"(a[3]), "r"(b0), "r"(b1));
}
__device__ __forceinline__ uint32_t mapa(uint32_t a, uint32_t cta) {
    uint32_t r;
    asm("mapa.shared::cluster.u32 %0, %1, %2;" : "=r"(r) : "r"(a), "r"(cta));
    return r;
}
__device__ __forceinline__ void st_async4(uint32_t rb, int off, int bar, float a, float b, float c, float d) {
    asm volatile("st.async.weak.shared::cluster.mbarrier::complete_tx::bytes.v4.f32 [%0], {%1,%2,%3,%4}, [%5];"
                 ::"r"(rb + off), "f"(a), "f"(b), "f"(c), "f"(d), "r"(rb + BARS + bar * 8) : "memory");
}
__device__ __forceinline__ void st_async2(uint32_t rb, int off, int bar, float a, float b) {
    asm volatile("st.async.weak.shared::cluster.mbarrier::complete_tx::bytes.v2.f32 [%0], {%1,%2}, [%3];"
                 ::"r"(rb + off), "f"(a), "f"(b), "r"(rb + BARS + bar * 8) : "memory");
}
__device__ __forceinline__ void bar_sync(int id, int n) { asm volatile("bar.sync %0, %1;" ::"r"(id), "r"(n) : "memory"); }
__device__ __forceinline__ void bar_arrive(int id, int n) { asm volatile("bar.arrive %0, %1;" ::"r"(id), "r"(n) : "memory"); }
__device__ __forceinline__ void cluster_wait() { asm volatile("barrier.cluster.wait.acquire.aligned;" ::: "memory"); }
__device__ __forceinline__ float4 lds128(uint32_t a) {
    float4 v;
    asm volatile("ld.shared.v4.f32 {%0,%1,%2,%3}, [%4];" : "=f"(v.x), "=f"(v.y), "=f"(v.z), "=f"(v.w) : "r"(a) : "memory");
    return v;
}
__device__ __forceinline__ float2 lds64(uint32_t a) {
    float2 v;
    asm volatile("ld.shared.v2.f32 {%0,%1}, [%2];" : "=f"(v.x), "=f"(v.y) : "r"(a) : "memory");
    return v;
}
__device__ __forceinline__ void sts16(uint32_t a, float v) {
    asm volatile("st.shared.u16 [%0], %1;" ::"r"(a), "h"(__bfloat16_as_ushort(__float2bfloat16_rn(v))) : "memory");
}
__device__ __forceinline__ float bfr(float v) { return __bfloat162float(__float2bfloat16_rn(v)); }
__device__ __forceinline__ float bf_lo(uint32_t w) { return __uint_as_float(w << 16); }
__device__ __forceinline__ float bf_hi(uint32_t w) { return __uint_as_float(w & 0xffff0000u); }
__device__ __forceinline__ uint32_t pack_bf(float lo, float hi) {
    __nv_bfloat162 v = __floats2bfloat162_rn(lo, hi);
    return *reinterpret_cast<uint32_t*>(&v);
}
__device__ __forceinline__ float wsum(float v) {
#pragma unroll
    for (int o = 16; o; o >>= 1) v += __shfl_xor_sync(0xffffffffu, v, o);
    return v;
}
__device__ __forceinline__ float wmax(float v) {
#pragma unroll
    for (int o = 16; o; o >>= 1) v = fmaxf(v, __shfl_xor_sync(0xffffffffu, v, o));
    return v;
}
__device__ __forceinline__ uint32_t sw64(uint32_t a) { return a ^ ((a >> 3) & 0x30u); }
__device__ __forceinline__ uint32_t sw128(uint32_t a) { return a ^ ((a >> 3) & 0x70u); }

__device__ __forceinline__ float lds_bf(uint32_t a) {
    uint16_t v;
    asm volatile("ld.shared.u16 %0, [%1];" : "=h"(v) : "r"(a) : "memory");
    return __uint_as_float((uint32_t)v << 16);
}
__device__ __forceinline__ float4 atom4(float* p, float a, float b, float c) {
    float4 o;
    asm volatile("atom.relaxed.gpu.global.add.v4.f32 {%0,%1,%2,%3}, [%4], {%5,%6,%7,%8};"
                 : "=f"(o.x), "=f"(o.y), "=f"(o.z), "=f"(o.w) : "l"(p), "f"(a), "f"(b), "f"(c), "f"(1.f) : "memory");
    return o;
}
__device__ __forceinline__ void finish(__nv_bfloat16* out, int r, int col, uint32_t epoch, float h0, float h1, float h2,
                                       float f0, float f1, float f2) {
    __nv_bfloat16* po = out + 96 * r + col;
    po[0] = __float2bfloat16_rn(h0 + bfr(f0));
    po[16] = __float2bfloat16_rn(h1 + bfr(f1));
    po[32] = __float2bfloat16_rn(h2 + bfr(f2));
    if (r == 0 && col == 0) g_epoch = epoch + 1;
}
__device__ __forceinline__ float4 sum6(uint32_t a, int stride) {
    float4 v[CL];
#pragma unroll
    for (int s = 0; s < CL; s++) v[s] = lds128(a + s * stride);
    return make_float4(((v[0].x + v[1].x) + (v[2].x + v[3].x)) + (v[4].x + v[5].x), ((v[0].y + v[1].y) + (v[2].y + v[3].y)) + (v[4].y + v[5].y),
                       ((v[0].z + v[1].z) + (v[2].z + v[3].z)) + (v[4].z + v[5].z), ((v[0].w + v[1].w) + (v[2].w + v[3].w)) + (v[4].w + v[5].w));
}
__device__ __forceinline__ float2 sum6h(uint32_t a, int stride) {
    float2 v[CL];
#pragma unroll
    for (int s = 0; s < CL; s++) v[s] = lds64(a + s * stride);
    return make_float2(((v[0].x + v[1].x) + (v[2].x + v[3].x)) + (v[4].x + v[5].x), ((v[0].y + v[1].y) + (v[2].y + v[3].y)) + (v[4].y + v[5].y));
}

template <int I>
__device__ __forceinline__ void produce(uint32_t sb, const CUtensorMap* mk, const CUtensorMap* mv, const CUtensorMap* mo,
                                        const CUtensorMap* m1, const CUtensorMap* m2, int c, int r, int key0, int nk,
                                        int lane, int& mine, int& landed, uint32_t t0) {
    if constexpr (I < NCHUNK) {
        constexpr int narrow = need_landed(I, by_phase(I, NARROW)), wide = need_landed(I, by_phase(I, WIDE));
        const uint32_t bar = sb + BARS + I * 8;
        if constexpr (narrow > 0) {
            int it = 0;
            while (landed < narrow) {
                const uint32_t m = mbar_test_ballot(sb + BARS, mine, I);
                landed += __popc(m);
                mine += ((m >> lane) & 1u) << 5;
                if constexpr (wide < narrow) {
                    uint32_t now;
                    asm volatile("mov.u32 %0, %%globaltimer_lo;" : "=r"(now));
                    if (landed >= wide && (int)(now - t0) >= nominal_ns(I)) break;
                }
                if (++it > 8 * SPIN_LIMIT) __trap();
            }
        }
        if constexpr (I == B_V + WQ_OFF / 8192) mbar_wait(sb + BARS + B_QDONE * 8);
        if constexpr (I == B_WO) mbar_wait(sb + BARS + B_KDONE * 8);
        if constexpr (I == B_W2) mbar_wait(sb + BARS + B_PVDONE * 8);
        if constexpr (I < B_V) {
            if (I - B_K < nk) tma3_elect(sb + R2 + (I - B_K) * 8192, mk, 0, key0 + (I - B_K) * 192, bar);
        } else if constexpr (I < B_WO) {
            if (I - B_V < nk) tma3_elect(sb + R1 + (I - B_V) * 8192, mv, 0, key0 + (I - B_V) * 192, bar);
        } else if constexpr (I < B_W1) {
            tma3_elect(sb + WO_OFF + (I - B_WO) * 6144, mo, 3 * r, 256 * c + (I - B_WO) * 32, bar);
        } else if constexpr (I < B_W2) {
            tma3_elect(sb + W1_OFF + (I - B_W1) * 9216, m1, 9 * c, 96 * r + (I - B_W1) * 16, bar);
        } else {
            tma3_elect(sb + R1 + (I - B_W2) * 6144, m2, 3 * r, 288 * c + (I - B_W2) * 32, bar);
        }
        produce<I + 1>(sb, mk, mv, mo, m1, m2, c, r, key0, nk, lane, mine, landed, t0);
    }
}

__global__ void __cluster_dims__(CL, 1, 1) __launch_bounds__(NTHREADS, 1)
decode_layer_kernel(const __nv_bfloat16* __restrict__ x, const __nv_bfloat16* __restrict__ wq, __nv_bfloat16* __restrict__ out,
                    const __grid_constant__ CUtensorMap mq, const __grid_constant__ CUtensorMap mk, const __grid_constant__ CUtensorMap mv,
                    const __grid_constant__ CUtensorMap mo, const __grid_constant__ CUtensorMap m1,
                    const __grid_constant__ CUtensorMap m2) {
    extern __shared__ __align__(1024) unsigned char smem[];
    const int tid = threadIdx.x, lane = tid & 31;
    const int c = blockIdx.y, r = blockIdx.x;
    if (tid < 384)
        asm volatile("prefetch.global.L2 [%0];" ::"l"(reinterpret_cast<const char*>(wq) + (size_t)(96 * r + (tid >> 2)) * (QD * 2) + c * 512 + (tid & 3) * 128));
    const int warp = __shfl_sync(0xffffffffu, tid >> 5, 0);
    const uint32_t sb = (uint32_t)__cvta_generic_to_shared(smem);
    const int nk = r < 4 ? 11 : 10;
    const int g = lane >> 2, t = lane & 3;

    if (warp == 13) {
        uint32_t t0;
        asm volatile("mov.u32 %0, %%globaltimer_lo;" : "=r"(t0));
        const int key0 = c * SK + (SK - WIN) + 32 * r;
        if (lane == 0) {
            asm volatile("prefetch.tensormap [%0];" ::"l"(&mq) : "memory");
            TLOG1(1);
#pragma unroll
            for (int b = 0; b < B_K; b++) {
                mbar_init(sb + BARS + b * 8, 1);
                mbar_expect(sb + BARS + b * 8, chunk_bytes(b));
            }
            mbar_init(sb + BARS + B_AR * 8, 5);
            asm volatile("fence.mbarrier_init.release.cluster;" ::: "memory");
            TLOG1(2);
#pragma unroll
            for (int i = 0; i < B_K; i++) tma3(sb + WQ_OFF + i * 8192, &mq, 96 * r + i * 16, 4 * c, sb + BARS + i * 8);
            asm volatile("prefetch.tensormap [%0];" ::"l"(&mk) : "memory");
            asm volatile("prefetch.tensormap [%0];" ::"l"(&mv) : "memory");
            asm volatile("prefetch.tensormap [%0];" ::"l"(&mo) : "memory");
            asm volatile("prefetch.tensormap [%0];" ::"l"(&m1) : "memory");
            asm volatile("prefetch.tensormap [%0];" ::"l"(&m2) : "memory");
            TLOG1(3);
        }
        __syncthreads();
        asm volatile("barrier.cluster.arrive.relaxed.aligned;" ::: "memory");
        TLOG(4);
        int mine = lane, landed = 0;
        produce<B_K>(sb, &mk, &mv, &mo, &m1, &m2, c, r, key0, nk, lane, mine, landed, t0);
        __syncwarp();
        TLOG(0);
        cluster_wait();
        TFLUSH();
        return;
    }

    if (warp == 12) {
        const uint32_t* x32 = reinterpret_cast<const uint32_t*>(x);
        uint32_t xr[9];
#pragma unroll
        for (int i = 0; i < 9; i++) xr[i] = __ldg(x32 + lane + 32 * i);
        const uint32_t xs0 = __ldg(x32 + 48 * r + lane), xs1 = __ldg(x32 + 48 * r + 32 + (lane & 15));
        const int col = 48 * (lane >> 4) + (lane & 15);
        const float x0 = __bfloat162float(x[96 * r + col]), x1 = __bfloat162float(x[96 * r + col + 16]), x2 = __bfloat162float(x[96 * r + col + 32]);
        __syncthreads();
        asm volatile("barrier.cluster.arrive.relaxed.aligned;" ::: "memory");
        float s = 0.f;
#pragma unroll
        for (int i = 0; i < 9; i++) s += bf_lo(xr[i]) + bf_hi(xr[i]);
        TLOG(2);
        const float mean = wsum(s) / DM;
        float v = 0.f;
#pragma unroll
        for (int i = 0; i < 9; i++) {
            const float a = bf_lo(xr[i]) - mean, b = bf_hi(xr[i]) - mean;
            v += a * a + b * b;
        }
        const float mb = bfr(mean), sd = bfr(sqrtf(bfr(bfr(wsum(v) / DM) + 1e-5f)));
        asm volatile("st.shared.u32 [%0], %1;" ::"r"(sb + XNV + lane * 4),
                     "r"(pack_bf(bfr(bf_lo(xs0) - mb) / sd, bfr(bf_hi(xs0) - mb) / sd)) : "memory");
        asm volatile("st.shared.u32 [%0], %1;" ::"r"(sb + XNV + 128 + (lane & 15) * 4),
                     "r"(pack_bf(bfr(bf_lo(xs1) - mb) / sd, bfr(bf_hi(xs1) - mb) / sd)) : "memory");
        bar_arrive(1, 288);
        TLOG(0);
        uint32_t epoch;
        asm volatile("ld.global.u32 %0, [%1];" : "=r"(epoch) : "l"(&g_epoch) : "memory");
        const uint32_t par = epoch & 1u;
        if (c == 0) {
            *reinterpret_cast<float4*>(&g_acc[par ^ 1][0][r][lane * 4]) = make_float4(0.f, 0.f, 0.f, 0.f);
            *reinterpret_cast<float4*>(&g_acc[par ^ 1][1][r][lane * 4]) = make_float4(0.f, 0.f, 0.f, 0.f);
        }
        cluster_wait();
        mbar_wait(sb + BARS + B_B * 8);
        float a0, a1, a2, n;
        int it = 0;
        do {
            asm volatile("ld.relaxed.gpu.global.v4.f32 {%0,%1,%2,%3}, [%4];" : "=f"(a0), "=f"(a1), "=f"(a2), "=f"(n) : "l"(&g_acc[par][0][r][lane * 4]) : "memory");
            if (++it > SPIN_LIMIT) __trap();
        } while (n != N_ATT);
        const float h0 = bfr(x0 + bfr(a0)), h1 = bfr(x1 + bfr(a1)), h2 = bfr(x2 + bfr(a2));
        sts16(sb + HV + col * 2, h0); sts16(sb + HV + col * 2 + 32, h1); sts16(sb + HV + col * 2 + 64, h2);
        __syncwarp();
        if (lane == 0) mbar_arrive(sb + BARS + B_H * 8);
        TLOG(9);
        const float ctr = __shfl_sync(0xffffffffu, h0, 0);
        const float d0 = h0 - ctr, d1 = h1 - ctr, d2 = h2 - ctr;
        float s1 = d0 + d1 + d2, s2 = d0 * d0 + d1 * d1 + d2 * d2;
#pragma unroll
        for (int o = 16; o; o >>= 1) {
            s1 += __shfl_xor_sync(0xffffffffu, s1, o);
            s2 += __shfl_xor_sync(0xffffffffu, s2, o);
        }
        if (lane < CL) st_async2(mapa(sb, lane), INST + r * 8, B_ST, ctr + s1 * (1.f / 96.f), s2 - s1 * s1 * (1.f / 96.f));
        TLOG(10);
        if (c == 3) {
            const float4 o = atom4(&g_acc[par][1][r][lane * 4], h0, h1, h2);
            if (o.w == N_OUT - 1.f) finish(out, r, col, epoch, h0, h1, h2, o.x, o.y, o.z);
        }
        TFLUSH();
        return;
    }

    if (warp < 11) {
        const int b0 = B_K + 5 * warp;
        if (lane == 0) {
#pragma unroll
            for (int i = 0; i < 5; i++) {
                const int b = b0 + i;
                mbar_init(sb + BARS + b * 8, b == B_KDONE ? 11 : (b == B_QDONE || b == B_PVDONE) ? 8 : 1);
            }
        }
        __syncwarp();
        const int b = b0 + lane;
        if (lane < 5 && b < B_QDONE) {
            const uint32_t bytes = b < NCHUNK ? chunk_bytes(b) : b == B_ML ? 1056 : b == B_ST ? 48 : (b == B_A || b == B_B) ? 6144 : 6912;
            mbar_expect(sb + BARS + b * 8, (nk == 10 && (b == B_K + 10 || b == B_V + 10)) ? 0 : bytes);
        }
        asm volatile("fence.mbarrier_init.release.cluster;" ::: "memory");
    }
    __syncthreads();
    asm volatile("barrier.cluster.arrive.relaxed.aligned;" ::: "memory");
    TLOG(7);
    uint32_t epoch = 0;
    if (warp < 6) asm volatile("ld.global.u32 %0, [%1];" : "=r"(epoch) : "l"(&g_epoch) : "memory");
    const uint32_t rb0 = mapa(sb, t), rb1 = mapa(sb, 4 + (t & 1));
    const int trow = (lane & 7) + 8 * (lane >> 4), tcol = (lane >> 3) & 1;

    if (warp < 8) {
        bar_sync(1, 288);
        uint32_t b[3][4];
#pragma unroll
        for (int u = 0; u < 3; u++) ldsm4(b[u], sb + XNV + u * 64 + (lane >> 3) * 16);
        float acc[2][4] = {};
#pragma unroll
        for (int s = 0; s < 6; s++) {
            mbar_wait(sb + BARS + (B_WQ + s) * 8);
#pragma unroll
            for (int n = 0; n < 2; n++) {
                uint32_t a[4];
                ldsm4t(a, sb + WQ_OFF + s * 8192 + (warp >> 1) * 2048 + sw128(trow * 128 + (4 * (warp & 1) + 2 * n + tcol) * 16));
                mma(acc[n], a, b[s >> 1][(s & 1) * 2], b[s >> 1][(s & 1) * 2 + 1]);
            }
        }
        TLOG(0);
        cluster_wait();
        const int off = INA + r * 1024 + (warp * 8 + g) * 16;
        st_async4(rb0, off, B_A, acc[0][0], acc[0][2], acc[1][0], acc[1][2]);
        if (t < 2) st_async4(rb1, off, B_A, acc[0][0], acc[0][2], acc[1][0], acc[1][2]);
        if (lane == 0) mbar_arrive(sb + BARS + B_QDONE * 8);
    } else {
        cluster_wait();
        if (warp < 10) {
            const int i = tid - 256;
            mbar_wait_cl(sb + BARS + B_A * 8);
            const float4 v = sum6(sb + INA + i * 16, 1024);
            const int n = 32 * (i >> 3) + (i & 7);
            const uint32_t a = sb + QV + (n >> 7) * 272 + (n & 127) * 2;
            sts16(a, v.x); sts16(a + 16, v.y); sts16(a + 32, v.z); sts16(a + 48, v.w);
        }
    }

    if (warp < 11) {
        bar_sync(2, 352);
        TLOG(1);
        float s0 = -INFINITY, s1 = -INFINITY, m0 = -INFINITY, m1v = -INFINITY, e0 = 0.f, e1 = 0.f, l0 = 0.f, l1 = 0.f;
        if (warp < nk) {
            uint32_t b[4][4];
#pragma unroll
            for (int u = 0; u < 4; u++) ldsm4(b[u], sb + QV + (lane & 1) * 272 + (4 * u + (lane >> 3)) * 16);
            float acc[2][4] = {};
            mbar_wait(sb + BARS + (B_K + warp) * 8);
            TLOG(2);
            const uint32_t krow = ((lane & 7) + 8 * ((lane >> 3) & 1)) * 256 + (lane >> 4) * 16;
#pragma unroll
            for (int s = 0; s < 8; s++) {
#pragma unroll
                for (int n = 0; n < 2; n++) {
                    uint32_t a[4];
                    ldsm4(a, sb + R2 + warp * 8192 + sw128(krow + n * 4096 + s * 32));
                    mma(acc[n], a, b[s >> 1][(s & 1) * 2], b[s >> 1][(s & 1) * 2 + 1]);
                }
            }
            const float r0 = t == 0 ? acc[0][0] : t == 1 ? acc[0][2] : t == 2 ? acc[1][0] : acc[1][2];
            const float r1 = t == 0 ? acc[0][1] : t == 1 ? acc[0][3] : t == 2 ? acc[1][1] : acc[1][3];
            s0 = bfr(bfr(r0) * 0.08838834764831845f);
            s1 = bfr(bfr(r1) * 0.08838834764831845f);
            m0 = wmax(s0); m1v = wmax(s1);
            e0 = __expf(s0 - m0); e1 = __expf(s1 - m1v);
            l0 = wsum(e0); l1 = wsum(e1);
        }
        if (lane == 0) mbar_arrive(sb + BARS + B_KDONE * 8);
        if (lane < CL) st_async4(mapa(sb, lane), INML + (r * 11 + warp) * 16, B_ML, m0, m1v, l0, l1);
        mbar_wait_cl(sb + BARS + B_ML * 8);
        if (warp < nk) {
            const float4 u0 = lds128(sb + INML + lane * 16), u1 = lds128(sb + INML + (lane + 32) * 16);
            float4 u2 = make_float4(-INFINITY, -INFINITY, 0.f, 0.f);
            if (lane < 2) u2 = lds128(sb + INML + (lane + 64) * 16);
            const float M0 = wmax(fmaxf(fmaxf(u0.x, u1.x), u2.x)), M1 = wmax(fmaxf(fmaxf(u0.y, u1.y), u2.y));
            const float L0 = wsum(u0.z * __expf(u0.x - M0) + u1.z * __expf(u1.x - M0) + u2.z * __expf(u2.x - M0));
            const float L1 = wsum(u0.w * __expf(u0.y - M1) + u1.w * __expf(u1.y - M1) + u2.w * __expf(u2.y - M1));
            const uint32_t a = sb + PVV + (32 * warp + 8 * t + g) * 2;
            sts16(a, e0 * (__expf(m0 - M0) / L0));
            sts16(a + 704, e1 * (__expf(m1v - M1) / L1));
        }
        TLOG(3);
    }

    if (warp < 8) {
        bar_sync(3, 352);
        float acc[2][4] = {};
        const uint32_t vrow = trow * 256 + (2 * warp + tcol) * 16;
#pragma unroll
        for (int j = 0; j < 11; j++) {
            if (j < nk) {
                uint32_t b[4], a0[4], a1[4];
                ldsm4(b, sb + PVV + (lane & 1) * 704 + j * 64 + (lane >> 3) * 16);
                mbar_wait(sb + BARS + (B_V + j) * 8);
                ldsm4t(a0, sb + R1 + j * 8192 + sw128(vrow));
                ldsm4t(a1, sb + R1 + j * 8192 + 4096 + sw128(vrow));
                mma(acc[0], a0, b[0], b[1]);
                mma(acc[1], a1, b[2], b[3]);
            }
        }
        const float v0 = acc[0][0] + acc[1][0], v1 = acc[0][1] + acc[1][1], v2 = acc[0][2] + acc[1][2], v3 = acc[0][3] + acc[1][3];
        const int off = INB + r * 1024 + (warp * 8 + g) * 16;
        st_async4(rb0, off, B_B, v0, v1, v2, v3);
        if (t < 2) st_async4(rb1, off, B_B, v0, v1, v2, v3);
        if (lane == 0) mbar_arrive(sb + BARS + B_PVDONE * 8);
        TLOG(4);
    } else if (warp < 11) {
        bar_arrive(3, 352);
        if (warp < 10) {
            const int i = tid - 256;
            mbar_wait_cl(sb + BARS + B_B * 8);
            const float4 v = sum6(sb + INB + i * 16, 1024);
            const uint32_t a = sb + OV + (16 * (i >> 3) + (i & 7)) * 2;
            sts16(a, v.x); sts16(a + 256, v.y); sts16(a + 16, v.z); sts16(a + 272, v.w);
            bar_arrive(4, 256);
            TLOG(5);
        }
    }

    if (warp < 6) {
        const int half = warp & 1, kg = warp >> 1;
        const uint32_t wrow = trow * 192 + (6 * half + tcol) * 16;
        const uint32_t wa[3] = {sw64(wrow), sw64(wrow + 32), sw64(wrow + 64)};
        float* accC = &g_acc[epoch & 1u][0][r][(half * 16 + (t & 1) * 8 + g) * 4];
        {
            bar_sync(4, 256);
            TLOG(5);
            float acc[3][2][4] = {};
#pragma unroll
            for (int i = 0; i < 3; i++) {
                const int j = kg + 3 * i;
                if (j < 8) {
                    uint32_t b[4];
                    ldsm4(b, sb + OV + j * 64 + (lane >> 3) * 16);
                    mbar_wait(sb + BARS + (B_WO + j) * 8);
#pragma unroll
                    for (int n = 0; n < 3; n++) {
                        uint32_t a0[4], a1[4];
                        ldsm4t(a0, sb + WO_OFF + j * 6144 + wa[n]);
                        ldsm4t(a1, sb + WO_OFF + j * 6144 + 3072 + wa[n]);
                        mma(acc[n][0], a0, b[0], b[1]);
                        mma(acc[n][1], a1, b[2], b[3]);
                    }
                }
            }
            float v[3];
#pragma unroll
            for (int n = 0; n < 3; n++) v[n] = t == 0 ? acc[n][0][0] + acc[n][1][0] : acc[n][0][2] + acc[n][1][2];
            if (t < 2)
                asm volatile("red.relaxed.gpu.global.add.v4.f32 [%0], {%1,%2,%3,%4};" ::"l"(accC), "f"(v[0]), "f"(v[1]), "f"(v[2]), "f"(1.f) : "memory");
            TLOG(6);
        }
        uint32_t a[2][3][2][4], b[3][4];
#pragma unroll
        for (int i = 0; i < 2; i++) {
            const int j = kg + 3 * i;
            mbar_wait(sb + BARS + (B_W2 + j) * 8);
#pragma unroll
            for (int n = 0; n < 3; n++) {
                ldsm4t(a[i][n][0], sb + R1 + j * 6144 + wa[n]);
                ldsm4t(a[i][n][1], sb + R1 + j * 6144 + 3072 + wa[n]);
            }
        }
        TLOG(11);
        mbar_wait(sb + BARS + B_AR * 8);
        TLOG(12);
#pragma unroll
        for (int i = 0; i < 3; i++) ldsm4(b[i], sb + AV + (kg + 3 * i) * 64 + (lane >> 3) * 16);
        const int col = 48 * half + 8 * (t & 1) + g;
        const float h0 = lds_bf(sb + HV + col * 2), h1 = lds_bf(sb + HV + col * 2 + 32), h2 = lds_bf(sb + HV + col * 2 + 64);
        float acc[3][2][4] = {};
#pragma unroll
        for (int i = 0; i < 2; i++)
#pragma unroll
            for (int n = 0; n < 3; n++) {
                mma(acc[n][0], a[i][n][0], b[i][0], b[i][1]);
                mma(acc[n][1], a[i][n][1], b[i][2], b[i][3]);
            }
        mbar_spin(sb + BARS + (B_W2 + kg + 6) * 8);
#pragma unroll
        for (int n = 0; n < 3; n++) {
            ldsm4t(a[0][n][0], sb + R1 + (kg + 6) * 6144 + wa[n]);
            ldsm4t(a[0][n][1], sb + R1 + (kg + 6) * 6144 + 3072 + wa[n]);
        }
#pragma unroll
        for (int n = 0; n < 3; n++) {
            mma(acc[n][0], a[0][n][0], b[2][0], b[2][1]);
            mma(acc[n][1], a[0][n][1], b[2][2], b[2][3]);
        }
        TLOG(13);
        if (t < 2) {
            float v[3];
#pragma unroll
            for (int n = 0; n < 3; n++) v[n] = t == 0 ? acc[n][0][0] + acc[n][1][0] : acc[n][0][2] + acc[n][1][2];
            const float4 o = atom4(accC + CL * 128, v[0], v[1], v[2]);
            if (o.w == N_OUT - 1.f) finish(out, r, col, epoch, h0, h1, h2, (o.x + v[0]) - h0, (o.y + v[1]) - h1, (o.z + v[2]) - h2);
        }
        __syncwarp();
        TLOG(8);
    } else {
        {
            const int w = warp - 6;
            uint32_t a[3][6][4];
            float cs[3][4] = {}, p[3][2][4] = {};
            const uint32_t arow = trow * 576 + (6 * w + tcol) * 16;
            auto send = [&](int box, int bar, float v0, float v1, float v2, float v3, float v4, float v5) {
                const int off4 = box + r * 1152 + (w * 8 + g) * 16, off2 = box + r * 1152 + 768 + (w * 8 + g) * 8;
                st_async4(rb0, off4, bar, v0, v1, v2, v3);
                st_async2(rb0, off2, bar, v4, v5);
                if (t < 2) {
                    st_async4(rb1, off4, bar, v0, v1, v2, v3);
                    st_async2(rb1, off2, bar, v4, v5);
                }
            };
#pragma unroll
            for (int s = 0; s < 6; s++) {
                mbar_wait(sb + BARS + (B_W1 + s) * 8);
#pragma unroll
                for (int n = 0; n < 3; n++) {
                    ldsm4t(a[n][s], sb + W1_OFF + s * 9216 + sw64(arow + n * 32));
                    mma(cs[n], a[n][s], 0x3f803f80u, 0x3f803f80u);
                }
            }
            send(INP2, B_P2, cs[0][0], cs[0][2], cs[1][0], cs[1][2], cs[2][0], cs[2][2]);
            TLOG(8);
            mbar_wait(sb + BARS + B_H * 8);
            TLOG(9);
#pragma unroll
            for (int u = 0; u < 3; u++) {
                uint32_t b[4];
                ldsm4(b, sb + HV + u * 64 + (lane >> 3) * 16);
#pragma unroll
                for (int n = 0; n < 3; n++) {
                    mma(p[n][0], a[n][2 * u], b[0], b[1]);
                    mma(p[n][1], a[n][2 * u + 1], b[2], b[3]);
                }
            }
            send(INP1, B_P1, p[0][0][0] + p[0][1][0], p[0][0][2] + p[0][1][2], p[1][0][0] + p[1][1][0], p[1][0][2] + p[1][1][2],
                 p[2][0][0] + p[2][1][0], p[2][0][2] + p[2][1][2]);
            TLOG(10);
        }
        if (warp < 11) {
            const int i = min(tid - 192, 143);
            mbar_wait_cl(sb + BARS + B_P2 * 8);
            const float2 cs = sum6h(sb + INP2 + i * 8, 1152);
            mbar_wait_cl(sb + BARS + B_ST * 8);
            const float2 st = ln_stats(sb + INST);
            const float mb = st.x, rs = st.y;
            mbar_wait_cl(sb + BARS + B_P1 * 8);
            TLOG(11);
            const float2 p = sum6h(sb + INP1 + i * 8, 1152);
            const float y0 = bfr((p.x - mb * cs.x) * rs), y1 = bfr((p.y - mb * cs.y) * rs);
            const uint32_t a = sb + AV + (i < 96 ? 48 * (i >> 4) + 16 * (i & 1) + ((i >> 1) & 7) : 48 * ((i - 96) >> 3) + 32 + (i & 7)) * 2;
            sts16(a, __fdividef(y0, 1.f + __expf(-y0)));
            sts16(a + 16, __fdividef(y1, 1.f + __expf(-y1)));
            __syncwarp();
            if (lane == 0) mbar_arrive(sb + BARS + B_AR * 8);
            TLOG(12);
        }
    }
    TFLUSH();
}

__device__ float f_q[QD], f_o[QD], f_h[DM], f_a[FF];

__device__ __forceinline__ float block_sum(float v, float* red) {
    v = wsum(v);
    __syncthreads();
    if ((threadIdx.x & 31) == 0) red[threadIdx.x >> 5] = v;
    __syncthreads();
    float s = 0.f;
    for (int i = 0; i < (int)(blockDim.x >> 5); i++) s += red[i];
    return s;
}
__device__ void fb_ln(const __nv_bfloat16* xb, const float* xf, float* xn, float* red) {
    float s = 0.f;
    for (int i = threadIdx.x; i < DM; i += blockDim.x) { xn[i] = xb ? __bfloat162float(xb[i]) : xf[i]; s += xn[i]; }
    const float mean = block_sum(s, red) / DM;
    float v = 0.f;
    for (int i = threadIdx.x; i < DM; i += blockDim.x) v += (xn[i] - mean) * (xn[i] - mean);
    const float sd = bfr(sqrtf(bfr(bfr(block_sum(v, red) / DM) + 1e-5f))), mb = bfr(mean);
    for (int i = threadIdx.x; i < DM; i += blockDim.x) xn[i] = bfr(bfr(xn[i] - mb) / sd);
    __syncthreads();
}
__global__ void fb_ln_gemv(const __nv_bfloat16* x, const __nv_bfloat16* w, int n, int mode) {
    __shared__ float xn[DM], red[8];
    fb_ln(mode == 0 ? x : nullptr, f_h, xn, red);
    const int j = blockIdx.x * blockDim.x + threadIdx.x;
    float s = 0.f;
    for (int k = 0; k < DM; k++) s += xn[k] * __bfloat162float(w[(size_t)k * n + j]);
    s = bfr(s);
    if (mode == 0) f_q[j] = s; else f_a[j] = bfr(s / (1.f + __expf(-s)));
}
__global__ void fb_attn(const __nv_bfloat16* kc, const __nv_bfloat16* vc) {
    __shared__ float p[WIN], red[8];
    const int h = blockIdx.x;
    const size_t base = ((size_t)(h >> 1) * SK + (SK - WIN)) * DH;
    float mx = -INFINITY;
    for (int k = threadIdx.x; k < WIN; k += blockDim.x) {
        float s = 0.f;
        for (int d = 0; d < DH; d++) s += f_q[h * DH + d] * __bfloat162float(kc[base + (size_t)k * DH + d]);
        p[k] = bfr(bfr(s) * 0.08838834764831845f);
        mx = fmaxf(mx, p[k]);
    }
    mx = wmax(mx);
    if ((threadIdx.x & 31) == 0) red[threadIdx.x >> 5] = mx;
    __syncthreads();
    for (int i = 0; i < (int)(blockDim.x >> 5); i++) mx = fmaxf(mx, red[i]);
    float l = 0.f;
    for (int k = threadIdx.x; k < WIN; k += blockDim.x) { p[k] = __expf(p[k] - mx); l += p[k]; }
    l = block_sum(l, red);
    float o = 0.f;
    for (int k = 0; k < WIN; k++) o += bfr(p[k] / l) * __bfloat162float(vc[base + (size_t)k * DH + threadIdx.x]);
    f_o[h * DH + threadIdx.x] = bfr(o);
}
__global__ void fb_out_gemv(const __nv_bfloat16* x, const __nv_bfloat16* w, int rows, int mode, __nv_bfloat16* out) {
    __shared__ float red[8][32];
    const int j = blockIdx.x * 32 + (threadIdx.x & 31);
    const float* v = mode == 0 ? f_o : f_a;
    float s = 0.f;
    for (int k = threadIdx.x >> 5; k < rows; k += 8) s += v[k] * __bfloat162float(w[(size_t)k * DM + j]);
    red[threadIdx.x >> 5][threadIdx.x & 31] = s;
    __syncthreads();
    if (threadIdx.x < 32) {
        s = 0.f;
        for (int i = 0; i < 8; i++) s += red[i][threadIdx.x];
        if (mode == 0) f_h[j] = bfr(__bfloat162float(x[j]) + bfr(s)); else out[j] = __float2bfloat16_rn(f_h[j] + bfr(s));
    }
}

typedef CUresult (*EncodeFn)(CUtensorMap*, CUtensorMapDataType, cuuint32_t, void*, const cuuint64_t*, const cuuint64_t*,
                             const cuuint32_t*, const cuuint32_t*, CUtensorMapInterleave, CUtensorMapSwizzle,
                             CUtensorMapL2promotion, CUtensorMapFloatOOBfill);

bool make_map(EncodeFn enc, CUtensorMap* m, const void* p, int rows, int cols, int inner, int groups, int boxrows,
              bool rows_first = false) {
    const int a = rows_first ? 2 : 1, b = 3 - a;
    cuuint64_t dim[3], str[3];
    cuuint32_t box[3];
    dim[0] = inner; dim[a] = cols / inner; dim[b] = rows;
    str[a - 1] = inner * 2; str[b - 1] = cols * 2;
    box[0] = inner; box[a] = groups; box[b] = boxrows;
    const cuuint32_t es[3] = {1, 1, 1};
    return enc(m, CU_TENSOR_MAP_DATA_TYPE_BFLOAT16, 3, const_cast<void*>(p), dim, str, box, es, CU_TENSOR_MAP_INTERLEAVE_NONE,
               inner == 64 ? CU_TENSOR_MAP_SWIZZLE_128B : CU_TENSOR_MAP_SWIZZLE_64B, CU_TENSOR_MAP_L2_PROMOTION_NONE,
               CU_TENSOR_MAP_FLOAT_OOB_FILL_NONE) == CUDA_SUCCESS;
}

}

extern "C" void kernel_launch(void* const* d_in, const int* in_sizes, int n_in, void* d_out, int out_size) {
    const __nv_bfloat16* x = (const __nv_bfloat16*)d_in[0];
    const __nv_bfloat16* kc = (const __nv_bfloat16*)d_in[1];
    const __nv_bfloat16* vc = (const __nv_bfloat16*)d_in[2];
    const __nv_bfloat16* wq = (const __nv_bfloat16*)d_in[3];
    const __nv_bfloat16* wo = (const __nv_bfloat16*)d_in[4];
    const __nv_bfloat16* w1 = (const __nv_bfloat16*)d_in[6];
    const __nv_bfloat16* w2 = (const __nv_bfloat16*)d_in[7];
    __nv_bfloat16* out = (__nv_bfloat16*)d_out;
    cudaStream_t stream = cudaStreamPerThread;

    static int state = 0;
    static EncodeFn enc = nullptr;
    if (state == 0) {
        state = 2;
        void* fn = nullptr;
        cudaDriverEntryPointQueryResult qr;
        if (cudaGetDriverEntryPoint("cuTensorMapEncodeTiled", &fn, cudaEnableDefault, &qr) == cudaSuccess &&
            qr == cudaDriverEntryPointSuccess && fn &&
            cudaFuncSetAttribute(decode_layer_kernel, cudaFuncAttributeMaxDynamicSharedMemorySize, SMEM_BYTES) == cudaSuccess) {
            enc = (EncodeFn)fn;
            cudaLaunchConfig_t cfg = {};
            cfg.gridDim = dim3(CL, HKV); cfg.blockDim = dim3(NTHREADS); cfg.dynamicSmemBytes = SMEM_BYTES;
            cudaLaunchAttribute at[1];
            at[0].id = cudaLaunchAttributeClusterDimension;
            at[0].val.clusterDim.x = CL; at[0].val.clusterDim.y = 1; at[0].val.clusterDim.z = 1;
            cfg.attrs = at; cfg.numAttrs = 1;
            int nc = 0;
            if (cudaOccupancyMaxActiveClusters(&nc, decode_layer_kernel, &cfg) == cudaSuccess && nc >= HKV) state = 1;
        }
        (void)cudaGetLastError();
    }
    CUtensorMap mq, mk, mv, mo, m1, m2;
    if (state == 1 && make_map(enc, &mq, wq, DM, QD, 64, 4, 16, true) && make_map(enc, &mk, kc, HKV * SK, DH, 64, 2, 32) && make_map(enc, &mv, vc, HKV * SK, DH, 64, 2, 32) &&
        make_map(enc, &mo, wo, QD, DM, 32, 3, 32) && make_map(enc, &m1, w1, DM, FF, 32, 9, 16) &&
        make_map(enc, &m2, w2, FF, DM, 32, 3, 32)) {
        decode_layer_kernel<<<dim3(CL, HKV), NTHREADS, SMEM_BYTES, stream>>>(x, wq, out, mq, mk, mv, mo, m1, m2);
        return;
    }
    fb_ln_gemv<<<QD / 128, 128, 0, stream>>>(x, wq, QD, 0);
    fb_attn<<<2 * HKV, 128, 0, stream>>>(kc, vc);
    fb_out_gemv<<<DM / 32, 256, 0, stream>>>(x, wo, QD, 0, out);
    fb_ln_gemv<<<FF / 128, 128, 0, stream>>>(x, w1, FF, 1);
    fb_out_gemv<<<DM / 32, 256, 0, stream>>>(x, w2, FF, 1, out);
}
```

```cpp
#include <cuda_runtime.h>
#include <cuda_bf16.h>
#include <cuda.h>
#include <stdint.h>

namespace {

constexpr int DM = 576, HKV = 16, SK = 8192, WIN = 2048, DH = 128, FF = 4608, QD = 4096;
constexpr int CL = 6;
constexpr int NWARPS = 14;
constexpr int NTHREADS = NWARPS * 32;

constexpr int R1 = 0;
constexpr int WQ_OFF = 90112 - 6 * 8192;
constexpr int R2 = 90112;
constexpr int WO_OFF = R2;
constexpr int W1_OFF = R2 + 49152;
constexpr int INA = R2 + 104448;
constexpr int INB = INA + 6144;
constexpr int INP2 = INB + 6144;
constexpr int INP1 = INP2 + 6912;
constexpr int INML = INP1 + 6912;
constexpr int INST = INML + 1088;
constexpr int XNV = INST + 64;
constexpr int QV = XNV + 192;
constexpr int PVV = QV + 544;
constexpr int OV = PVV + 1408;
constexpr int HV = OV + 512;
constexpr int AV = HV + 192;
constexpr int BARS = AV + 576;
constexpr int SMEM_BYTES = BARS + 64 * 8;
static_assert(SMEM_BYTES <= 232448 - 2048, "smem");

constexpr int B_WQ = 0, B_K = 6, B_V = 17, B_WO = 28, B_W1 = 36, B_W2 = 42, NCHUNK = 51;
constexpr int B_A = 51, B_ML = 52, B_B = 53, B_P2 = 54, B_ST = 55, B_P1 = 56;
constexpr int B_QDONE = 57, B_KDONE = 58, B_PVDONE = 59, B_H = 60, B_AR = 61, NBAR = 62;

__host__ __device__ constexpr int chunk_bytes(int i) {
    return i < B_WO ? 8192 : i < B_W1 ? 6144 : i < B_W2 ? 9216 : 6144;
}
#define NARROW 6440383836LL
#define WIDE 6464645644LL
#define PACE_PS 478
#define PACE_T0 550
__host__ __device__ constexpr int by_phase(int i, long long w) {
    return 1024 * (int)(w / (i < B_V ? 100000000 : i < B_WO ? 1000000 : i < B_W1 ? 10000 : i < B_W2 ? 100 : 1) % 100);
}
__host__ __device__ constexpr int need_landed(int i, int w) {
    int s = 0, j = i;
    while (j >= 0 && s + chunk_bytes(j) <= w) { s += chunk_bytes(j); j--; }
    return j + 1;
}
__host__ __device__ constexpr int nominal_ns(int i) {
    int cum = -44 * 1024 - (i >= B_V ? 2731 : 0) - (i >= B_WO ? 2731 : 0);
    for (int j = 0; j <= i; j++) cum += chunk_bytes(j);
    return PACE_T0 + cum / 16 * PACE_PS / 1000;
}

constexpr float N_ATT = 16.f;
constexpr float N_OUT = 49.f;
__device__ __align__(1024) float g_acc[2][2][CL][128];
__device__ uint32_t g_epoch;

#define TLOG(i) do {} while (0)
#define TFLUSH() do {} while (0)
#define TLOG1(i) do {} while (0)

__device__ __forceinline__ float bfr(float v) {
    uint32_t w;
    asm("cvt.rn.bf16x2.f32 %0, %1, %2;" : "=r"(w) : "f"(v), "f"(0.f));
    return __uint_as_float(w);
}
__device__ __forceinline__ void mbar_init(uint32_t a, uint32_t c) {
    asm volatile("mbarrier.init.shared::cta.b64 [%0], %1;" ::"r"(a), "r"(c) : "memory");
}
__device__ __forceinline__ void mbar_expect(uint32_t a, uint32_t b) {
    asm volatile("mbarrier.arrive.expect_tx.shared::cta.b64 _, [%0], %1;" ::"r"(a), "r"(b) : "memory");
}
__device__ __forceinline__ void mbar_arrive(uint32_t a) {
    asm volatile("mbarrier.arrive.shared::cta.b64 _, [%0];" ::"r"(a) : "memory");
}
constexpr int SPIN_LIMIT = 1 << 21;
__device__ __forceinline__ void mbar_wait(uint32_t a) {
    uint32_t ok;
    int it = 0;
    do {
        asm volatile("{\n.reg .pred p;\nmbarrier.try_wait.parity.shared::cta.b64 p, [%1], 0;\nselp.u32 %0, 1, 0, p;\n}"
                     : "=r"(ok) : "r"(a) : "memory");
        if (++it > SPIN_LIMIT) __trap();
    } while (!ok);
}
__device__ __forceinline__ void mbar_spin(uint32_t a) {
    uint32_t ok;
    int it = 0;
    do {
        asm volatile("{\n.reg .pred p;\nmbarrier.test_wait.parity.shared::cta.b64 p, [%1], 0;\nselp.u32 %0, 1, 0, p;\n}"
                     : "=r"(ok) : "r"(a) : "memory");
        if (++it > 8 * SPIN_LIMIT) __trap();
    } while (!ok);
}
__device__ __forceinline__ float2 ln_stats(uint32_t a) {
    float4 u[3];
#pragma unroll
    for (int i = 0; i < 3; i++)
        asm volatile("ld.shared.v4.f32 {%0,%1,%2,%3}, [%4];" : "=f"(u[i].x), "=f"(u[i].y), "=f"(u[i].z), "=f"(u[i].w) : "r"(a + 16 * i) : "memory");
    const float mean = ((u[0].x + u[0].z) + (u[1].x + u[1].z) + (u[2].x + u[2].z)) * (1.f / 6.f);
    const float d0 = u[0].x - mean, d1 = u[0].z - mean, d2 = u[1].x - mean, d3 = u[1].z - mean, d4 = u[2].x - mean, d5 = u[2].z - mean;
    const float var = (((u[0].y + u[0].w) + (u[1].y + u[1].w) + (u[2].y + u[2].w)) +
                       96.f * ((d0 * d0 + d1 * d1) + (d2 * d2 + d3 * d3) + (d4 * d4 + d5 * d5))) * (1.f / 576.f);
    return make_float2(bfr(mean), 1.f / bfr(sqrtf(bfr(bfr(var) + 1e-5f))));
}
__device__ __forceinline__ uint32_t mbar_test_ballot(uint32_t bars, int idx, int lim) {
    uint32_t m;
    asm volatile("{\n.reg .pred p, q;\n.reg .u32 a;\nsetp.lt.s32 q, %2, %3;\nsetp.ne.u32 p, 0, 0;\nmad.lo.u32 a, %2, 8, %1;\n"
                 "@q mbarrier.test_wait.parity.shared::cta.b64 p, [a], 0;\nvote.sync.ballot.b32 %0, p, 0xffffffff;\n}"
                 : "=r"(m) : "r"(bars), "r"(idx), "r"(lim) : "memory");
    return m;
}
__device__ __forceinline__ void mbar_wait_cl(uint32_t a) {
    uint32_t ok;
    int it = 0;
    do {
        asm volatile("{\n.reg .pred p;\nmbarrier.try_wait.parity.acquire.cluster.shared::cta.b64 p, [%1], 0;\nselp.u32 %0, 1, 0, p;\n}"
                     : "=r"(ok) : "r"(a) : "memory");
        if (++it > SPIN_LIMIT) __trap();
    } while (!ok);
}
__device__ __forceinline__ void tma3(uint32_t dst, const CUtensorMap* m, int c1, int c2, uint32_t bar) {
    asm volatile("cp.async.bulk.tensor.3d.shared::cluster.global.mbarrier::complete_tx::bytes [%0], [%1, {%2, %3, %4}], [%5];"
                 ::"r"(dst), "l"(m), "r"(0), "r"(c1), "r"(c2), "r"(bar) : "memory");
}
__device__ __forceinline__ void tma3_elect(uint32_t dst, const CUtensorMap* m, int c1, int c2, uint32_t bar) {
    asm volatile("{\n.reg .pred p;\nelect.sync _|p, 0xffffffff;\n"
                 "@p cp.async.bulk.tensor.3d.shared::cluster.global.mbarrier::complete_tx::bytes [%0], [%1, {%2, %3, %4}], [%5];\n}"
                 ::"r"(dst), "l"(m), "r"(0), "r"(c1), "r"(c2), "r"(bar) : "memory");
}
__device__ __forceinline__ void ldsm4(uint32_t (&r)[4], uint32_t a) {
    asm volatile("ldmatrix.sync.aligned.m8n8.x4.shared.b16 {%0,%1,%2,%3}, [%4];"
                 : "=r"(r[0]), "=r"(r[1]), "=r"(r[2]), "=r"(r[3]) : "r"(a) : "memory");
}
__device__ __forceinline__ void ldsm4t(uint32_t (&r)[4], uint32_t a) {
    asm volatile("ldmatrix.sync.aligned.m8n8.x4.trans.shared.b16 {%0,%1,%2,%3}, [%4];"
                 : "=r"(r[0]), "=r"(r[1]), "=r"(r[2]), "=r"(r[3]) : "r"(a) : "memory");
}
__device__ __forceinline__ void mma(float (&c)[4], const uint32_t (&a)[4], uint32_t b0, uint32_t b1) {
    asm("mma.sync.aligned.m16n8k16.row.col.f32.bf16.bf16.f32 {%0,%1,%2,%3}, {%4,%5,%6,%7}, {%8,%9}, {%0,%1,%2,%3};"
        : "+f"(c[0]), "+f"(c[1]), "+f"(c[2]), "+f"(c[3])
        : "r"(a[0]), "r"(a[1]), "r"(a[2]), "r"(a[3]), "r"(b0), "r"(b1));
}
__device__ __forceinline__ uint32_t mapa(uint32_t a, uint32_t cta) {
    uint32_t r;
    asm("mapa.shared::cluster.u32 %0, %1, %2;" : "=r"(r) : "r"(a), "r"(cta));
    return r;
}
__device__ __forceinline__ void st_async4(uint32_t rb, int off, int bar, float a, float b, float c, float d) {
    asm volatile("st.async.weak.shared::cluster.mbarrier::complete_tx::bytes.v4.f32 [%0], {%1,%2,%3,%4}, [%5];"
                 ::"r"(rb + off), "f"(a), "f"(b), "f"(c), "f"(d), "r"(rb + BARS + bar * 8) : "memory");
}
__device__ __forceinline__ void st_async2(uint32_t rb, int off, int bar, float a, float b) {
    asm volatile("st.async.weak.shared::cluster.mbarrier::complete_tx::bytes.v2.f32 [%0], {%1,%2}, [%3];"
                 ::"r"(rb + off), "f"(a), "f"(b), "r"(rb + BARS + bar * 8) : "memory");
}
__device__ __forceinline__ void bar_sync(int id, int n) { asm volatile("bar.sync %0, %1;" ::"r"(id), "r"(n) : "memory"); }
__device__ __forceinline__ void bar_arrive(int id, int n) { asm volatile("bar.arrive %0, %1;" ::"r"(id), "r"(n) : "memory"); }
__device__ __forceinline__ void cluster_wait() { asm volatile("barrier.cluster.wait.acquire.aligned;" ::: "memory"); }
__device__ __forceinline__ float4 lds128(uint32_t a) {
    float4 v;
    asm volatile("ld.shared.v4.f32 {%0,%1,%2,%3}, [%4];" : "=f"(v.x), "=f"(v.y), "=f"(v.z), "=f"(v.w) : "r"(a) : "memory");
    return v;
}
__device__ __forceinline__ float2 lds64(uint32_t a) {
    float2 v;
    asm volatile("ld.shared.v2.f32 {%0,%1}, [%2];" : "=f"(v.x), "=f"(v.y) : "r"(a) : "memory");
    return v;
}
__device__ __forceinline__ void sts16(uint32_t a, float v) {
    asm volatile("st.shared.u16 [%0], %1;" ::"r"(a), "h"(__bfloat16_as_ushort(__float2bfloat16_rn(v))) : "memory");
}
__device__ __forceinline__ float bf_lo(uint32_t w) { return __uint_as_float(w << 16); }
__device__ __forceinline__ float bf_hi(uint32_t w) { return __uint_as_float(w & 0xffff0000u); }
__device__ __forceinline__ uint32_t pack_bf(float lo, float hi) {
    __nv_bfloat162 v = __floats2bfloat162_rn(lo, hi);
    return *reinterpret_cast<uint32_t*>(&v);
}
__device__ __forceinline__ float wsum(float v) {
#pragma unroll
    for (int o = 16; o; o >>= 1) v += __shfl_xor_sync(0xffffffffu, v, o);
    return v;
}
__device__ __forceinline__ float wmax(float v) {
#pragma unroll
    for (int o = 16; o; o >>= 1) v = fmaxf(v, __shfl_xor_sync(0xffffffffu, v, o));
    return v;
}
__device__ __forceinline__ uint32_t sw64(uint32_t a) { return a ^ ((a >> 3) & 0x30u); }
__device__ __forceinline__ uint32_t sw128(uint32_t a) { return a ^ ((a >> 3) & 0x70u); }

__device__ __forceinline__ float lds_bf(uint32_t a) {
    uint16_t v;
    asm volatile("ld.shared.u16 %0, [%1];" : "=h"(v) : "r"(a) : "memory");
    return __uint_as_float((uint32_t)v << 16);
}
__device__ __forceinline__ float4 atom4(float* p, float a, float b, float c) {
    float4 o;
    asm volatile("atom.relaxed.gpu.global.add.v4.f32 {%0,%1,%2,%3}, [%4], {%5,%6,%7,%8};"
                 : "=f"(o.x), "=f"(o.y), "=f"(o.z), "=f"(o.w) : "l"(p), "f"(a), "f"(b), "f"(c), "f"(1.f) : "memory");
    return o;
}
__device__ __forceinline__ void finish(__nv_bfloat16* po, bool first, uint32_t epoch, float h0, float h1, float h2,
                                       float f0, float f1, float f2) {
    asm volatile("st.global.u16 [%0], %1;\nst.global.u16 [%0+32], %2;\nst.global.u16 [%0+64], %3;"
                 ::"l"(po), "h"(__bfloat16_as_ushort(__float2bfloat16_rn(h0 + bfr(f0)))),
                 "h"(__bfloat16_as_ushort(__float2bfloat16_rn(h1 + bfr(f1)))),
                 "h"(__bfloat16_as_ushort(__float2bfloat16_rn(h2 + bfr(f2)))) : "memory");
    if (first) g_epoch = epoch + 1;
}
__device__ __forceinline__ float4 sum6(uint32_t a, int stride) {
    float4 v[CL];
#pragma unroll
    for (int s = 0; s < CL; s++) v[s] = lds128(a + s * stride);
    return make_float4(((v[0].x + v[1].x) + (v[2].x + v[3].x)) + (v[4].x + v[5].x), ((v[0].y + v[1].y) + (v[2].y + v[3].y)) + (v[4].y + v[5].y),
                       ((v[0].z + v[1].z) + (v[2].z + v[3].z)) + (v[4].z + v[5].z), ((v[0].w + v[1].w) + (v[2].w + v[3].w)) + (v[4].w + v[5].w));
}
__device__ __forceinline__ float2 sum6h(uint32_t a, int stride) {
    float2 v[CL];
#pragma unroll
    for (int s = 0; s < CL; s++) v[s] = lds64(a + s * stride);
    return make_float2(((v[0].x + v[1].x) + (v[2].x + v[3].x)) + (v[4].x + v[5].x), ((v[0].y + v[1].y) + (v[2].y + v[3].y)) + (v[4].y + v[5].y));
}

template <int I>
__device__ __forceinline__ void produce(uint32_t sb, const CUtensorMap* mk, const CUtensorMap* mv, const CUtensorMap* mo,
                                        const CUtensorMap* m1, const CUtensorMap* m2, int c, int r, int key0, int nk,
                                        int lane, int& mine, int& landed, uint32_t t0) {
    if constexpr (I < NCHUNK) {
        constexpr int narrow = need_landed(I, by_phase(I, NARROW)), wide = need_landed(I, by_phase(I, WIDE));
        const uint32_t bar = sb + BARS + I * 8;
        if constexpr (narrow > 0) {
            int it = 0;
            while (landed < narrow) {
                const uint32_t m = mbar_test_ballot(sb + BARS, mine, I);
                landed += __popc(m);
                mine += ((m >> lane) & 1u) << 5;
                if constexpr (wide < narrow) {
                    uint32_t now;
                    asm volatile("mov.u32 %0, %%globaltimer_lo;" : "=r"(now));
                    if (landed >= wide && (int)(now - t0) >= nominal_ns(I)) break;
                }
                if (++it > 8 * SPIN_LIMIT) __trap();
            }
        }
        if constexpr (I == B_V + WQ_OFF / 8192) mbar_wait(sb + BARS + B_QDONE * 8);
        if constexpr (I == B_WO) mbar_wait(sb + BARS + B_KDONE * 8);
        if constexpr (I == B_W2) mbar_wait(sb + BARS + B_PVDONE * 8);
        if constexpr (I < B_V) {
            if (I - B_K < nk) tma3_elect(sb + R2 + (I - B_K) * 8192, mk, 0, key0 + (I - B_K) * 192, bar);
        } else if constexpr (I < B_WO) {
            if (I - B_V < nk) tma3_elect(sb + R1 + (I - B_V) * 8192, mv, 0, key0 + (I - B_V) * 192, bar);
        } else if constexpr (I < B_W1) {
            tma3_elect(sb + WO_OFF + (I - B_WO) * 6144, mo, 3 * r, 256 * c + (I - B_WO) * 32, bar);
        } else if constexpr (I < B_W2) {
            tma3_elect(sb + W1_OFF + (I - B_W1) * 9216, m1, 9 * c, 96 * r + (I - B_W1) * 16, bar);
        } else {
            tma3_elect(sb + R1 + (I - B_W2) * 6144, m2, 3 * r, 288 * c + (I - B_W2) * 32, bar);
        }
        produce<I + 1>(sb, mk, mv, mo, m1, m2, c, r, key0, nk, lane, mine, landed, t0);
    }
}

__global__ void __cluster_dims__(CL, 1, 1) __launch_bounds__(NTHREADS, 1)
decode_layer_kernel(const __nv_bfloat16* __restrict__ x, const __nv_bfloat16* __restrict__ wq, __nv_bfloat16* __restrict__ out,
                    const __grid_constant__ CUtensorMap mq, const __grid_constant__ CUtensorMap mk, const __grid_constant__ CUtensorMap mv,
                    const __grid_constant__ CUtensorMap mo, const __grid_constant__ CUtensorMap m1,
                    const __grid_constant__ CUtensorMap m2) {
    extern __shared__ __align__(1024) unsigned char smem[];
    const int tid = threadIdx.x, lane = tid & 31;
    const int c = blockIdx.y, r = blockIdx.x;
    asm volatile("{\n.reg .pred p;\nsetp.lt.u32 p, %1, 384;\n@p prefetch.global.L2 [%0];\n}"
                 ::"l"(reinterpret_cast<const char*>(wq) + (uint32_t)(r * (96 * QD * 2) + c * 512 + (tid >> 2) * (QD * 2) + (tid & 3) * 128)), "r"(tid));
    const int warp = __shfl_sync(0xffffffffu, tid >> 5, 0);
    const uint32_t sb = (uint32_t)__cvta_generic_to_shared(smem);
    const int nk = r < 4 ? 11 : 10;
    const int g = lane >> 2, t = lane & 3;

    if (warp == 13) {
        uint32_t t0;
        asm volatile("mov.u32 %0, %%globaltimer_lo;" : "=r"(t0));
        const int key0 = c * SK + (SK - WIN) + 32 * r;
        if (lane == 0) {
            asm volatile("prefetch.tensormap [%0];" ::"l"(&mq) : "memory");
            TLOG1(1);
#pragma unroll
            for (int b = 0; b < B_K; b++) {
                mbar_init(sb + BARS + b * 8, 1);
                mbar_expect(sb + BARS + b * 8, chunk_bytes(b));
            }
            mbar_init(sb + BARS + B_AR * 8, 5);
            asm volatile("fence.mbarrier_init.release.cluster;" ::: "memory");
            TLOG1(2);
#pragma unroll
            for (int i = 0; i < B_K; i++) tma3(sb + WQ_OFF + i * 8192, &mq, 96 * r + i * 16, 4 * c, sb + BARS + i * 8);
            asm volatile("prefetch.tensormap [%0];" ::"l"(&mk) : "memory");
            asm volatile("prefetch.tensormap [%0];" ::"l"(&mv) : "memory");
            asm volatile("prefetch.tensormap [%0];" ::"l"(&mo) : "memory");
            asm volatile("prefetch.tensormap [%0];" ::"l"(&m1) : "memory");
            asm volatile("prefetch.tensormap [%0];" ::"l"(&m2) : "memory");
            TLOG1(3);
        }
        __syncthreads();
        asm volatile("barrier.cluster.arrive.relaxed.aligned;" ::: "memory");
        TLOG(4);
        int mine = lane, landed = 0;
        produce<B_K>(sb, &mk, &mv, &mo, &m1, &m2, c, r, key0, nk, lane, mine, landed, t0);
        __syncwarp();
        TLOG(0);
        cluster_wait();
        TFLUSH();
        return;
    }

    if (warp == 12) {
        const uint32_t* x32 = reinterpret_cast<const uint32_t*>(x);
        uint32_t xr[9];
#pragma unroll
        for (int i = 0; i < 9; i++) xr[i] = __ldg(x32 + lane + 32 * i);
        const uint32_t xs0 = __ldg(x32 + 48 * r + lane), xs1 = __ldg(x32 + 48 * r + 32 + (lane & 15));
        const int col = 48 * (lane >> 4) + (lane & 15);
        const float x0 = __bfloat162float(x[96 * r + col]), x1 = __bfloat162float(x[96 * r + col + 16]), x2 = __bfloat162float(x[96 * r + col + 32]);
        __syncthreads();
        asm volatile("barrier.cluster.arrive.relaxed.aligned;" ::: "memory");
        float s = 0.f;
#pragma unroll
        for (int i = 0; i < 9; i++) s += bf_lo(xr[i]) + bf_hi(xr[i]);
        TLOG(2);
        const float mean = wsum(s) / DM;
        float v = 0.f;
#pragma unroll
        for (int i = 0; i < 9; i++) {
            const float a = bf_lo(xr[i]) - mean, b = bf_hi(xr[i]) - mean;
            v += a * a + b * b;
        }
        const float mb = bfr(mean), sd = bfr(sqrtf(bfr(bfr(wsum(v) / DM) + 1e-5f)));
        asm volatile("st.shared.u32 [%0], %1;" ::"r"(sb + XNV + lane * 4),
                     "r"(pack_bf(bfr(bf_lo(xs0) - mb) / sd, bfr(bf_hi(xs0) - mb) / sd)) : "memory");
        asm volatile("st.shared.u32 [%0], %1;" ::"r"(sb + XNV + 128 + (lane & 15) * 4),
                     "r"(pack_bf(bfr(bf_lo(xs1) - mb) / sd, bfr(bf_hi(xs1) - mb) / sd)) : "memory");
        bar_arrive(1, 288);
        TLOG(0);
        uint32_t epoch;
        asm volatile("ld.global.u32 %0, [%1];" : "=r"(epoch) : "l"(&g_epoch) : "memory");
        const uint32_t par = epoch & 1u;
        if (c == 0) {
            *reinterpret_cast<float4*>(&g_acc[par ^ 1][0][r][lane * 4]) = make_float4(0.f, 0.f, 0.f, 0.f);
            *reinterpret_cast<float4*>(&g_acc[par ^ 1][1][r][lane * 4]) = make_float4(0.f, 0.f, 0.f, 0.f);
        }
        cluster_wait();
        mbar_wait(sb + BARS + B_B * 8);
        float a0, a1, a2, n;
        int it = 0;
        do {
            asm volatile("ld.relaxed.gpu.global.v4.f32 {%0,%1,%2,%3}, [%4];" : "=f"(a0), "=f"(a1), "=f"(a2), "=f"(n) : "l"(&g_acc[par][0][r][lane * 4]) : "memory");
            if (++it > SPIN_LIMIT) __trap();
        } while (n != N_ATT);
        const float h0 = bfr(x0 + bfr(a0)), h1 = bfr(x1 + bfr(a1)), h2 = bfr(x2 + bfr(a2));
        sts16(sb + HV + col * 2, h0); sts16(sb + HV + col * 2 + 32, h1); sts16(sb + HV + col * 2 + 64, h2);
        __syncwarp();
        if (lane == 0) mbar_arrive(sb + BARS + B_H * 8);
        TLOG(9);
        const float ctr = __shfl_sync(0xffffffffu, h0, 0);
        const float d0 = h0 - ctr, d1 = h1 - ctr, d2 = h2 - ctr;
        float s1 = d0 + d1 + d2, s2 = d0 * d0 + d1 * d1 + d2 * d2;
#pragma unroll
        for (int o = 16; o; o >>= 1) {
            s1 += __shfl_xor_sync(0xffffffffu, s1, o);
            s2 += __shfl_xor_sync(0xffffffffu, s2, o);
        }
        if (lane < CL) st_async2(mapa(sb, lane), INST + r * 8, B_ST, ctr + s1 * (1.f / 96.f), s2 - s1 * s1 * (1.f / 96.f));
        TLOG(10);
        if (c == 3) {
            const float4 o = atom4(&g_acc[par][1][r][lane * 4], h0, h1, h2);
            if (o.w == N_OUT - 1.f) finish(out + 96 * r + col, r == 0 && col == 0, epoch, h0, h1, h2, o.x, o.y, o.z);
        }
        TFLUSH();
        return;
    }

    if (warp < 11) {
        const int b0 = B_K + 5 * warp;
        if (lane == 0) {
#pragma unroll
            for (int i = 0; i < 5; i++) {
                const int b = b0 + i;
                mbar_init(sb + BARS + b * 8, b == B_KDONE ? 11 : (b == B_QDONE || b == B_PVDONE) ? 8 : 1);
            }
        }
        __syncwarp();
        const int b = b0 + lane;
        if (lane < 5 && b < B_QDONE) {
            const uint32_t bytes = b < NCHUNK ? chunk_bytes(b) : b == B_ML ? 1056 : b == B_ST ? 48 : (b == B_A || b == B_B) ? 6144 : 6912;
            mbar_expect(sb + BARS + b * 8, (nk == 10 && (b == B_K + 10 || b == B_V + 10)) ? 0 : bytes);
        }
        asm volatile("fence.mbarrier_init.release.cluster;" ::: "memory");
    }
    __syncthreads();
    asm volatile("barrier.cluster.arrive.relaxed.aligned;" ::: "memory");
    TLOG(7);
    uint32_t epoch = 0;
    if (warp < 6) asm volatile("ld.global.u32 %0, [%1];" : "=r"(epoch) : "l"(&g_epoch) : "memory");
    const uint32_t rb0 = mapa(sb, t), rb1 = mapa(sb, 4 + (t & 1));
    const int trow = (lane & 7) + 8 * (lane >> 4), tcol = (lane >> 3) & 1;

    if (warp < 8) {
        bar_sync(1, 288);
        uint32_t b[3][4];
#pragma unroll
        for (int u = 0; u < 3; u++) ldsm4(b[u], sb + XNV + u * 64 + (lane >> 3) * 16);
        float acc[2][4] = {};
#pragma unroll
        for (int s = 0; s < 6; s++) {
            mbar_wait(sb + BARS + (B_WQ + s) * 8);
#pragma unroll
            for (int n = 0; n < 2; n++) {
                uint32_t a[4];
                ldsm4t(a, sb + WQ_OFF + s * 8192 + (warp >> 1) * 2048 + sw128(trow * 128 + (4 * (warp & 1) + 2 * n + tcol) * 16));
                mma(acc[n], a, b[s >> 1][(s & 1) * 2], b[s >> 1][(s & 1) * 2 + 1]);
            }
        }
        TLOG(0);
        cluster_wait();
        const int off = INA + r * 1024 + (warp * 8 + g) * 16;
        st_async4(rb0, off, B_A, acc[0][0], acc[0][2], acc[1][0], acc[1][2]);
        if (t < 2) st_async4(rb1, off, B_A, acc[0][0], acc[0][2], acc[1][0], acc[1][2]);
        if (lane == 0) mbar_arrive(sb + BARS + B_QDONE * 8);
    } else {
        cluster_wait();
        if (warp < 10) {
            const int i = tid - 256;
            mbar_wait_cl(sb + BARS + B_A * 8);
            const float4 v = sum6(sb + INA + i * 16, 1024);
            const int n = 32 * (i >> 3) + (i & 7);
            const uint32_t a = sb + QV + (n >> 7) * 272 + (n & 127) * 2;
            sts16(a, v.x); sts16(a + 16, v.y); sts16(a + 32, v.z); sts16(a + 48, v.w);
        }
    }

    if (warp < 11) {
        bar_sync(2, 352);
        TLOG(1);
        float s0 = -INFINITY, s1 = -INFINITY, m0 = -INFINITY, m1v = -INFINITY, e0 = 0.f, e1 = 0.f, l0 = 0.f, l1 = 0.f;
        if (warp < nk) {
            uint32_t b[4][4];
#pragma unroll
            for (int u = 0; u < 4; u++) ldsm4(b[u], sb + QV + (lane & 1) * 272 + (4 * u + (lane >> 3)) * 16);
            float acc[2][4] = {};
            mbar_wait(sb + BARS + (B_K + warp) * 8);
            TLOG(2);
            const uint32_t krow = ((lane & 7) + 8 * ((lane >> 3) & 1)) * 256 + (lane >> 4) * 16;
#pragma unroll
            for (int s = 0; s < 8; s++) {
#pragma unroll
                for (int n = 0; n < 2; n++) {
                    uint32_t a[4];
                    ldsm4(a, sb + R2 + warp * 8192 + sw128(krow + n * 4096 + s * 32));
                    mma(acc[n], a, b[s >> 1][(s & 1) * 2], b[s >> 1][(s & 1) * 2 + 1]);
                }
            }
            const float r0 = t == 0 ? acc[0][0] : t == 1 ? acc[0][2] : t == 2 ? acc[1][0] : acc[1][2];
            const float r1 = t == 0 ? acc[0][1] : t == 1 ? acc[0][3] : t == 2 ? acc[1][1] : acc[1][3];
            s0 = bfr(bfr(r0) * 0.08838834764831845f);
            s1 = bfr(bfr(r1) * 0.08838834764831845f);
            m0 = wmax(s0); m1v = wmax(s1);
            e0 = __expf(s0 - m0); e1 = __expf(s1 - m1v);
            l0 = wsum(e0); l1 = wsum(e1);
        }
        if (lane == 0) mbar_arrive(sb + BARS + B_KDONE * 8);
        if (lane < CL) st_async4(mapa(sb, lane), INML + (r * 11 + warp) * 16, B_ML, m0, m1v, l0, l1);
        mbar_wait_cl(sb + BARS + B_ML * 8);
        if (warp < nk) {
            const float4 u0 = lds128(sb + INML + lane * 16), u1 = lds128(sb + INML + (lane + 32) * 16);
            float4 u2 = make_float4(-INFINITY, -INFINITY, 0.f, 0.f);
            if (lane < 2) u2 = lds128(sb + INML + (lane + 64) * 16);
            const float M0 = wmax(fmaxf(fmaxf(u0.x, u1.x), u2.x)), M1 = wmax(fmaxf(fmaxf(u0.y, u1.y), u2.y));
            const float L0 = wsum(u0.z * __expf(u0.x - M0) + u1.z * __expf(u1.x - M0) + u2.z * __expf(u2.x - M0));
            const float L1 = wsum(u0.w * __expf(u0.y - M1) + u1.w * __expf(u1.y - M1) + u2.w * __expf(u2.y - M1));
            const uint32_t a = sb + PVV + (32 * warp + 8 * t + g) * 2;
            sts16(a, e0 * (__expf(m0 - M0) / L0));
            sts16(a + 704, e1 * (__expf(m1v - M1) / L1));
        }
        TLOG(3);
    }

    if (warp < 8) {
        bar_sync(3, 352);
        float acc[2][4] = {};
        const uint32_t vrow = trow * 256 + (2 * warp + tcol) * 16;
#pragma unroll
        for (int j = 0; j < 11; j++) {
            if (j < nk) {
                uint32_t b[4], a0[4], a1[4];
                ldsm4(b, sb + PVV + (lane & 1) * 704 + j * 64 + (lane >> 3) * 16);
                mbar_wait(sb + BARS + (B_V + j) * 8);
                ldsm4t(a0, sb + R1 + j * 8192 + sw128(vrow));
                ldsm4t(a1, sb + R1 + j * 8192 + 4096 + sw128(vrow));
                mma(acc[0], a0, b[0], b[1]);
                mma(acc[1], a1, b[2], b[3]);
            }
        }
        const float v0 = acc[0][0] + acc[1][0], v1 = acc[0][1] + acc[1][1], v2 = acc[0][2] + acc[1][2], v3 = acc[0][3] + acc[1][3];
        const int off = INB + r * 1024 + (warp * 8 + g) * 16;
        st_async4(rb0, off, B_B, v0, v1, v2, v3);
        if (t < 2) st_async4(rb1, off, B_B, v0, v1, v2, v3);
        if (lane == 0) mbar_arrive(sb + BARS + B_PVDONE * 8);
        TLOG(4);
    } else if (warp < 11) {
        bar_arrive(3, 352);
        if (warp < 10) {
            const int i = tid - 256;
            mbar_wait_cl(sb + BARS + B_B * 8);
            const float4 v = sum6(sb + INB + i * 16, 1024);
            const uint32_t a = sb + OV + (16 * (i >> 3) + (i & 7)) * 2;
            sts16(a, v.x); sts16(a + 256, v.y); sts16(a + 16, v.z); sts16(a + 272, v.w);
            bar_arrive(4, 256);
            TLOG(5);
        }
    }

    if (warp < 6) {
        const int half = warp & 1, kg = warp >> 1;
        const uint32_t wrow = trow * 192 + (6 * half + tcol) * 16;
        const uint32_t wa[3] = {sw64(wrow), sw64(wrow + 32), sw64(wrow + 64)};
        float* accC = &g_acc[epoch & 1u][0][r][(half * 16 + (t & 1) * 8 + g) * 4];
        asm volatile("" ::"l"(accC) : "memory");
        {
            bar_sync(4, 256);
            TLOG(5);
            float acc[3][2][4] = {};
#pragma unroll
            for (int i = 0; i < 3; i++) {
                const int j = kg + 3 * i;
                if (j < 8) {
                    uint32_t b[4];
                    ldsm4(b, sb + OV + j * 64 + (lane >> 3) * 16);
                    mbar_wait(sb + BARS + (B_WO + j) * 8);
#pragma unroll
                    for (int n = 0; n < 3; n++) {
                        uint32_t a0[4], a1[4];
                        ldsm4t(a0, sb + WO_OFF + j * 6144 + wa[n]);
                        ldsm4t(a1, sb + WO_OFF + j * 6144 + 3072 + wa[n]);
                        mma(acc[n][0], a0, b[0], b[1]);
                        mma(acc[n][1], a1, b[2], b[3]);
                    }
                }
            }
            float v[3];
#pragma unroll
            for (int n = 0; n < 3; n++) v[n] = t == 0 ? acc[n][0][0] + acc[n][1][0] : acc[n][0][2] + acc[n][1][2];
            const uint32_t slot = sb + INA + (half * 16 + (t & 1) * 8 + g) * 16;
            if (kg > 0) {
                if (t < 2) asm volatile("st.shared.v4.f32 [%0], {%1,%2,%3,%3};" ::"r"(slot + kg * 512), "f"(v[0]), "f"(v[1]), "f"(v[2]) : "memory");
                bar_arrive(5, 192);
            } else {
                bar_sync(5, 192);
                const float4 u1 = lds128(slot + 512), u2 = lds128(slot + 1024);
                if (t < 2)
                    asm volatile("red.relaxed.gpu.global.add.v4.f32 [%0], {%1,%2,%3,%4};"
                                 ::"l"(accC), "f"(v[0] + u1.x + u2.x), "f"(v[1] + u1.y + u2.y), "f"(v[2] + u1.z + u2.z), "f"(1.f) : "memory");
            }
            TLOG(6);
        }
        uint32_t a[2][3][2][4], b[3][4];
#pragma unroll
        for (int i = 0; i < 2; i++) {
            const int j = kg + 3 * i;
            mbar_wait(sb + BARS + (B_W2 + j) * 8);
#pragma unroll
            for (int n = 0; n < 3; n++) {
                ldsm4t(a[i][n][0], sb + R1 + j * 6144 + wa[n]);
                ldsm4t(a[i][n][1], sb + R1 + j * 6144 + 3072 + wa[n]);
            }
        }
        TLOG(11);
        mbar_wait(sb + BARS + B_AR * 8);
        TLOG(12);
#pragma unroll
        for (int i = 0; i < 3; i++) ldsm4(b[i], sb + AV + (kg + 3 * i) * 64 + (lane >> 3) * 16);
        const int col = 48 * half + 8 * (t & 1) + g;
        const float h0 = lds_bf(sb + HV + col * 2), h1 = lds_bf(sb + HV + col * 2 + 32), h2 = lds_bf(sb + HV + col * 2 + 64);
        __nv_bfloat16* po = out + 96 * r + col;
        asm volatile("" : "+l"(po));
        float acc[3][2][4] = {};
#pragma unroll
        for (int i = 0; i < 2; i++)
#pragma unroll
            for (int n = 0; n < 3; n++) {
                mma(acc[n][0], a[i][n][0], b[i][0], b[i][1]);
                mma(acc[n][1], a[i][n][1], b[i][2], b[i][3]);
            }
        mbar_spin(sb + BARS + (B_W2 + kg + 6) * 8);
#pragma unroll
        for (int n = 0; n < 3; n++) {
            ldsm4t(a[0][n][0], sb + R1 + (kg + 6) * 6144 + wa[n]);
            ldsm4t(a[0][n][1], sb + R1 + (kg + 6) * 6144 + 3072 + wa[n]);
        }
#pragma unroll
        for (int n = 0; n < 3; n++) {
            mma(acc[n][0], a[0][n][0], b[2][0], b[2][1]);
            mma(acc[n][1], a[0][n][1], b[2][2], b[2][3]);
        }
        TLOG(13);
        if (t < 2) {
            float v[3];
#pragma unroll
            for (int n = 0; n < 3; n++) v[n] = t == 0 ? acc[n][0][0] + acc[n][1][0] : acc[n][0][2] + acc[n][1][2];
            const float4 o = atom4(accC + CL * 128, v[0], v[1], v[2]);
            if (o.w == N_OUT - 1.f) finish(po, r == 0 && col == 0, epoch, h0, h1, h2, o.x + (v[0] - h0), o.y + (v[1] - h1), o.z + (v[2] - h2));
        }
        __syncwarp();
        TLOG(8);
    } else {
        {
            const int w = warp - 6;
            uint32_t a[3][6][4];
            float cs[3][4] = {}, p[3][2][4] = {};
            const uint32_t arow = trow * 576 + (6 * w + tcol) * 16;
            auto send = [&](int box, int bar, float v0, float v1, float v2, float v3, float v4, float v5) {
                const int off4 = box + r * 1152 + (w * 8 + g) * 16, off2 = box + r * 1152 + 768 + (w * 8 + g) * 8;
                st_async4(rb0, off4, bar, v0, v1, v2, v3);
                st_async2(rb0, off2, bar, v4, v5);
                if (t < 2) {
                    st_async4(rb1, off4, bar, v0, v1, v2, v3);
                    st_async2(rb1, off2, bar, v4, v5);
                }
            };
#pragma unroll
            for (int s = 0; s < 6; s++) {
                mbar_wait(sb + BARS + (B_W1 + s) * 8);
#pragma unroll
                for (int n = 0; n < 3; n++) {
                    ldsm4t(a[n][s], sb + W1_OFF + s * 9216 + sw64(arow + n * 32));
                    mma(cs[n], a[n][s], 0x3f803f80u, 0x3f803f80u);
                }
            }
            send(INP2, B_P2, cs[0][0], cs[0][2], cs[1][0], cs[1][2], cs[2][0], cs[2][2]);
            TLOG(8);
            mbar_wait(sb + BARS + B_H * 8);
            TLOG(9);
#pragma unroll
            for (int u = 0; u < 3; u++) {
                uint32_t b[4];
                ldsm4(b, sb + HV + u * 64 + (lane >> 3) * 16);
#pragma unroll
                for (int n = 0; n < 3; n++) {
                    mma(p[n][0], a[n][2 * u], b[0], b[1]);
                    mma(p[n][1], a[n][2 * u + 1], b[2], b[3]);
                }
            }
            send(INP1, B_P1, p[0][0][0] + p[0][1][0], p[0][0][2] + p[0][1][2], p[1][0][0] + p[1][1][0], p[1][0][2] + p[1][1][2],
                 p[2][0][0] + p[2][1][0], p[2][0][2] + p[2][1][2]);
            TLOG(10);
        }
        if (warp < 11) {
            const int i = min(tid - 192, 143);
            mbar_wait_cl(sb + BARS + B_P2 * 8);
            const float2 cs = sum6h(sb + INP2 + i * 8, 1152);
            mbar_wait_cl(sb + BARS + B_ST * 8);
            const float2 st = ln_stats(sb + INST);
            const float mb = st.x, rs = st.y;
            mbar_wait_cl(sb + BARS + B_P1 * 8);
            TLOG(11);
            const float2 p = sum6h(sb + INP1 + i * 8, 1152);
            const float y0 = bfr((p.x - mb * cs.x) * rs), y1 = bfr((p.y - mb * cs.y) * rs);
            const uint32_t a = sb + AV + (i < 96 ? 48 * (i >> 4) + 16 * (i & 1) + ((i >> 1) & 7) : 48 * ((i - 96) >> 3) + 32 + (i & 7)) * 2;
            sts16(a, __fdividef(y0, 1.f + __expf(-y0)));
            sts16(a + 16, __fdividef(y1, 1.f + __expf(-y1)));
            __syncwarp();
            if (lane == 0) mbar_arrive(sb + BARS + B_AR * 8);
            TLOG(12);
        }
    }
    TFLUSH();
}

__device__ float f_q[QD], f_o[QD], f_h[DM], f_a[FF];

__device__ __forceinline__ float block_sum(float v, float* red) {
    v = wsum(v);
    __syncthreads();
    if ((threadIdx.x & 31) == 0) red[threadIdx.x >> 5] = v;
    __syncthreads();
    float s = 0.f;
    for (int i = 0; i < (int)(blockDim.x >> 5); i++) s += red[i];
    return s;
}
__device__ void fb_ln(const __nv_bfloat16* xb, const float* xf, float* xn, float* red) {
    float s = 0.f;
    for (int i = threadIdx.x; i < DM; i += blockDim.x) { xn[i] = xb ? __bfloat162float(xb[i]) : xf[i]; s += xn[i]; }
    const float mean = block_sum(s, red) / DM;
    float v = 0.f;
    for (int i = threadIdx.x; i < DM; i += blockDim.x) v += (xn[i] - mean) * (xn[i] - mean);
    const float sd = bfr(sqrtf(bfr(bfr(block_sum(v, red) / DM) + 1e-5f))), mb = bfr(mean);
    for (int i = threadIdx.x; i < DM; i += blockDim.x) xn[i] = bfr(bfr(xn[i] - mb) / sd);
    __syncthreads();
}
__global__ void fb_ln_gemv(const __nv_bfloat16* x, const __nv_bfloat16* w, int n, int mode) {
    __shared__ float xn[DM], red[8];
    fb_ln(mode == 0 ? x : nullptr, f_h, xn, red);
    const int j = blockIdx.x * blockDim.x + threadIdx.x;
    float s = 0.f;
    for (int k = 0; k < DM; k++) s += xn[k] * __bfloat162float(w[(size_t)k * n + j]);
    s = bfr(s);
    if (mode == 0) f_q[j] = s; else f_a[j] = bfr(s / (1.f + __expf(-s)));
}
__global__ void fb_attn(const __nv_bfloat16* kc, const __nv_bfloat16* vc) {
    __shared__ float p[WIN], red[8];
    const int h = blockIdx.x;
    const size_t base = ((size_t)(h >> 1) * SK + (SK - WIN)) * DH;
    float mx = -INFINITY;
    for (int k = threadIdx.x; k < WIN; k += blockDim.x) {
        float s = 0.f;
        for (int d = 0; d < DH; d++) s += f_q[h * DH + d] * __bfloat162float(kc[base + (size_t)k * DH + d]);
        p[k] = bfr(bfr(s) * 0.08838834764831845f);
        mx = fmaxf(mx, p[k]);
    }
    mx = wmax(mx);
    if ((threadIdx.x & 31) == 0) red[threadIdx.x >> 5] = mx;
    __syncthreads();
    for (int i = 0; i < (int)(blockDim.x >> 5); i++) mx = fmaxf(mx, red[i]);
    float l = 0.f;
    for (int k = threadIdx.x; k < WIN; k += blockDim.x) { p[k] = __expf(p[k] - mx); l += p[k]; }
    l = block_sum(l, red);
    float o = 0.f;
    for (int k = 0; k < WIN; k++) o += bfr(p[k] / l) * __bfloat162float(vc[base + (size_t)k * DH + threadIdx.x]);
    f_o[h * DH + threadIdx.x] = bfr(o);
}
__global__ void fb_out_gemv(const __nv_bfloat16* x, const __nv_bfloat16* w, int rows, int mode, __nv_bfloat16* out) {
    __shared__ float red[8][32];
    const int j = blockIdx.x * 32 + (threadIdx.x & 31);
    const float* v = mode == 0 ? f_o : f_a;
    float s = 0.f;
    for (int k = threadIdx.x >> 5; k < rows; k += 8) s += v[k] * __bfloat162float(w[(size_t)k * DM + j]);
    red[threadIdx.x >> 5][threadIdx.x & 31] = s;
    __syncthreads();
    if (threadIdx.x < 32) {
        s = 0.f;
        for (int i = 0; i < 8; i++) s += red[i][threadIdx.x];
        if (mode == 0) f_h[j] = bfr(__bfloat162float(x[j]) + bfr(s)); else out[j] = __float2bfloat16_rn(f_h[j] + bfr(s));
    }
}

typedef CUresult (*EncodeFn)(CUtensorMap*, CUtensorMapDataType, cuuint32_t, void*, const cuuint64_t*, const cuuint64_t*,
                             const cuuint32_t*, const cuuint32_t*, CUtensorMapInterleave, CUtensorMapSwizzle,
                             CUtensorMapL2promotion, CUtensorMapFloatOOBfill);

bool make_map(EncodeFn enc, CUtensorMap* m, const void* p, int rows, int cols, int inner, int groups, int boxrows,
              bool rows_first = false) {
    const int a = rows_first ? 2 : 1, b = 3 - a;
    cuuint64_t dim[3], str[3];
    cuuint32_t box[3];
    dim[0] = inner; dim[a] = cols / inner; dim[b] = rows;
    str[a - 1] = inner * 2; str[b - 1] = cols * 2;
    box[0] = inner; box[a] = groups; box[b] = boxrows;
    const cuuint32_t es[3] = {1, 1, 1};
    return enc(m, CU_TENSOR_MAP_DATA_TYPE_BFLOAT16, 3, const_cast<void*>(p), dim, str, box, es, CU_TENSOR_MAP_INTERLEAVE_NONE,
               inner == 64 ? CU_TENSOR_MAP_SWIZZLE_128B : CU_TENSOR_MAP_SWIZZLE_64B, CU_TENSOR_MAP_L2_PROMOTION_NONE,
               CU_TENSOR_MAP_FLOAT_OOB_FILL_NONE) == CUDA_SUCCESS;
}

}

extern "C" void kernel_launch(void* const* d_in, const int* in_sizes, int n_in, void* d_out, int out_size) {
    const __nv_bfloat16* x = (const __nv_bfloat16*)d_in[0];
    const __nv_bfloat16* kc = (const __nv_bfloat16*)d_in[1];
    const __nv_bfloat16* vc = (const __nv_bfloat16*)d_in[2];
    const __nv_bfloat16* wq = (const __nv_bfloat16*)d_in[3];
    const __nv_bfloat16* wo = (const __nv_bfloat16*)d_in[4];
    const __nv_bfloat16* w1 = (const __nv_bfloat16*)d_in[6];
    const __nv_bfloat16* w2 = (const __nv_bfloat16*)d_in[7];
    __nv_bfloat16* out = (__nv_bfloat16*)d_out;
    cudaStream_t stream = cudaStreamPerThread;

    static int state = 0;
    static EncodeFn enc = nullptr;
    if (state == 0) {
        state = 2;
        void* fn = nullptr;
        cudaDriverEntryPointQueryResult qr;
        if (cudaGetDriverEntryPoint("cuTensorMapEncodeTiled", &fn, cudaEnableDefault, &qr) == cudaSuccess &&
            qr == cudaDriverEntryPointSuccess && fn &&
            cudaFuncSetAttribute(decode_layer_kernel, cudaFuncAttributeMaxDynamicSharedMemorySize, SMEM_BYTES) == cudaSuccess) {
            enc = (EncodeFn)fn;
            cudaLaunchConfig_t cfg = {};
            cfg.gridDim = dim3(CL, HKV); cfg.blockDim = dim3(NTHREADS); cfg.dynamicSmemBytes = SMEM_BYTES;
            cudaLaunchAttribute at[1];
            at[0].id = cudaLaunchAttributeClusterDimension;
            at[0].val.clusterDim.x = CL; at[0].val.clusterDim.y = 1; at[0].val.clusterDim.z = 1;
            cfg.attrs = at; cfg.numAttrs = 1;
            int nc = 0;
            if (cudaOccupancyMaxActiveClusters(&nc, decode_layer_kernel, &cfg) == cudaSuccess && nc >= HKV) state = 1;
        }
        (void)cudaGetLastError();
    }
    CUtensorMap mq, mk, mv, mo, m1, m2;
    if (state == 1 && make_map(enc, &mq, wq, DM, QD, 64, 4, 16, true) && make_map(enc, &mk, kc, HKV * SK, DH, 64, 2, 32) && make_map(enc, &mv, vc, HKV * SK, DH, 64, 2, 32) &&
        make_map(enc, &mo, wo, QD, DM, 32, 3, 32) && make_map(enc, &m1, w1, DM, FF, 32, 9, 16) &&
        make_map(enc, &m2, w2, FF, DM, 32, 3, 32)) {
        decode_layer_kernel<<<dim3(CL, HKV), NTHREADS, SMEM_BYTES, stream>>>(x, wq, out, mq, mk, mv, mo, m1, m2);
        return;
    }
    fb_ln_gemv<<<QD / 128, 128, 0, stream>>>(x, wq, QD, 0);
    fb_attn<<<2 * HKV, 128, 0, stream>>>(kc, vc);
    fb_out_gemv<<<DM / 32, 256, 0, stream>>>(x, wo, QD, 0, out);
    fb_ln_gemv<<<FF / 128, 128, 0, stream>>>(x, w1, FF, 1);
    fb_out_gemv<<<DM / 32, 256, 0, stream>>>(x, w2, FF, 1, out);
}
```

```cpp
#include <cuda_runtime.h>
#include <cuda_bf16.h>
#include <cuda.h>
#include <stdint.h>

namespace {

constexpr int DM = 576, HKV = 16, SK = 8192, WIN = 2048, DH = 128, FF = 4608, QD = 4096;
constexpr int CL = 6;
constexpr int NWARPS = 14;
constexpr int NTHREADS = NWARPS * 32;

constexpr int R1 = 0;
constexpr int WQ_OFF = 90112 - 6 * 8192;
constexpr int R2 = 90112;
constexpr int WO_OFF = R2;
constexpr int W1_OFF = R2 + 49152;
constexpr int INA = R2 + 104448;
constexpr int INB = INA + 6144;
constexpr int INP2 = INB + 6144;
constexpr int INP1 = INP2 + 6912;
constexpr int INML = INP1 + 6912;
constexpr int INST = INML + 1088;
constexpr int XNV = INST + 64;
constexpr int QV = XNV + 192;
constexpr int PVV = QV + 544;
constexpr int OV = PVV + 1408;
constexpr int HV = OV + 512;
constexpr int AV = HV + 192;
constexpr int BARS = AV + 576;
constexpr int SMEM_BYTES = BARS + 64 * 8;
static_assert(SMEM_BYTES <= 232448, "smem");

constexpr int B_WQ = 0, B_K = 6, B_V = 17, B_WO = 28, B_W1 = 36, B_W2 = 42, NCHUNK = 51;
constexpr int B_A = 51, B_ML = 52, B_B = 53, B_P2 = 54, B_ST = 55, B_P1 = 56;
constexpr int B_QDONE = 57, B_KDONE = 58, B_PVDONE = 59, B_H = 60, B_AR = 61;
static_assert(B_K + 5 * 11 == B_AR && B_AR < 64, "barrier set-up below covers B_K .. B_H");

__host__ __device__ constexpr int chunk_bytes(int i) {
    return i < B_WO ? 8192 : i < B_W1 ? 6144 : i < B_W2 ? 9216 : 6144;
}
__host__ __device__ constexpr int by_phase(int i, int k, int v, int o, int a, int b) {
    return 1024 * (i < B_V ? k : i < B_WO ? v : i < B_W1 ? o : i < B_W2 ? a : b);
}
__host__ __device__ constexpr int narrow_window(int i) { return by_phase(i, 64, 40, 38, 38, 36); }
__host__ __device__ constexpr int wide_window(int i) { return by_phase(i, 64, 64, 64, 64, 48); }
constexpr int PACE_PS = 476;
constexpr int PACE_T0 = 550;
__host__ __device__ constexpr int need_landed(int i, int w) {
    int s = 0, j = i;
    while (j >= 0 && s + chunk_bytes(j) <= w) { s += chunk_bytes(j); j--; }
    return j + 1;
}
__host__ __device__ constexpr int nominal_ns(int i) {
    int cum = -44 * 1024 - (i >= B_V ? 2731 : 0) - (i >= B_WO ? 2731 : 0);
    for (int j = 0; j <= i; j++) cum += chunk_bytes(j);
    return PACE_T0 + cum / 16 * PACE_PS / 1000;
}

constexpr float N_ATT = 16.f;
constexpr float N_OUT = 49.f;
__device__ __align__(1024) float g_acc[2][2][CL][128];
__device__ uint32_t g_epoch;

__device__ __forceinline__ float bfr(float v) {
    uint32_t w;
    asm("cvt.rn.bf16x2.f32 %0, %1, %2;" : "=r"(w) : "f"(v), "f"(0.f));
    return __uint_as_float(w);
}
__device__ __forceinline__ void mbar_init(uint32_t a, uint32_t c) {
    asm volatile("mbarrier.init.shared::cta.b64 [%0], %1;" ::"r"(a), "r"(c) : "memory");
}
__device__ __forceinline__ void mbar_expect(uint32_t a, uint32_t b) {
    asm volatile("mbarrier.arrive.expect_tx.shared::cta.b64 _, [%0], %1;" ::"r"(a), "r"(b) : "memory");
}
__device__ __forceinline__ void mbar_arrive(uint32_t a) {
    asm volatile("mbarrier.arrive.shared::cta.b64 _, [%0];" ::"r"(a) : "memory");
}
constexpr int SPIN_LIMIT = 1 << 21;
__device__ __forceinline__ void mbar_wait(uint32_t a) {
    uint32_t ok;
    int it = 0;
    do {
        asm volatile("{\n.reg .pred p;\nmbarrier.try_wait.parity.shared::cta.b64 p, [%1], 0;\nselp.u32 %0, 1, 0, p;\n}"
                     : "=r"(ok) : "r"(a) : "memory");
        if (++it > SPIN_LIMIT) __trap();
    } while (!ok);
}
__device__ __forceinline__ void mbar_spin(uint32_t a) {
    uint32_t ok;
    int it = 0;
    do {
        asm volatile("{\n.reg .pred p;\nmbarrier.test_wait.parity.shared::cta.b64 p, [%1], 0;\nselp.u32 %0, 1, 0, p;\n}"
                     : "=r"(ok) : "r"(a) : "memory");
        if (++it > 8 * SPIN_LIMIT) __trap();
    } while (!ok);
}
__device__ __forceinline__ float2 ln_stats(uint32_t a) {
    float4 u[3];
#pragma unroll
    for (int i = 0; i < 3; i++)
        asm volatile("ld.shared.v4.f32 {%0,%1,%2,%3}, [%4];" : "=f"(u[i].x), "=f"(u[i].y), "=f"(u[i].z), "=f"(u[i].w) : "r"(a + 16 * i) : "memory");
    const float mean = ((u[0].x + u[0].z) + (u[1].x + u[1].z) + (u[2].x + u[2].z)) * (1.f / 6.f);
    const float d0 = u[0].x - mean, d1 = u[0].z - mean, d2 = u[1].x - mean, d3 = u[1].z - mean, d4 = u[2].x - mean, d5 = u[2].z - mean;
    const float var = (((u[0].y + u[0].w) + (u[1].y + u[1].w) + (u[2].y + u[2].w)) +
                       96.f * ((d0 * d0 + d1 * d1) + (d2 * d2 + d3 * d3) + (d4 * d4 + d5 * d5))) * (1.f / 576.f);
    return make_float2(bfr(mean), 1.f / bfr(sqrtf(bfr(bfr(var) + 1e-5f))));
}
__device__ __forceinline__ uint32_t mbar_test_ballot(uint32_t bars, int idx, int lim) {
    uint32_t m;
    asm volatile("{\n.reg .pred p, q;\n.reg .u32 a;\nsetp.lt.s32 q, %2, %3;\nsetp.ne.u32 p, 0, 0;\nmad.lo.u32 a, %2, 8, %1;\n"
                 "@q mbarrier.test_wait.parity.shared::cta.b64 p, [a], 0;\nvote.sync.ballot.b32 %0, p, 0xffffffff;\n}"
                 : "=r"(m) : "r"(bars), "r"(idx), "r"(lim) : "memory");
    return m;
}
__device__ __forceinline__ void mbar_wait_cl(uint32_t a) {
    uint32_t ok;
    int it = 0;
    do {
        asm volatile("{\n.reg .pred p;\nmbarrier.try_wait.parity.acquire.cluster.shared::cta.b64 p, [%1], 0;\nselp.u32 %0, 1, 0, p;\n}"
                     : "=r"(ok) : "r"(a) : "memory");
        if (++it > SPIN_LIMIT) __trap();
    } while (!ok);
}
__device__ __forceinline__ void tma3(uint32_t dst, const CUtensorMap* m, int c1, int c2, uint32_t bar) {
    asm volatile("cp.async.bulk.tensor.3d.shared::cluster.global.mbarrier::complete_tx::bytes [%0], [%1, {%2, %3, %4}], [%5];"
                 ::"r"(dst), "l"(m), "r"(0), "r"(c1), "r"(c2), "r"(bar) : "memory");
}
__device__ __forceinline__ void tma3_elect(uint32_t dst, const CUtensorMap* m, int c1, int c2, uint32_t bar) {
    asm volatile("{\n.reg .pred p;\nelect.sync _|p, 0xffffffff;\n"
                 "@p cp.async.bulk.tensor.3d.shared::cluster.global.mbarrier::complete_tx::bytes [%0], [%1, {%2, %3, %4}], [%5];\n}"
                 ::"r"(dst), "l"(m), "r"(0), "r"(c1), "r"(c2), "r"(bar) : "memory");
}
__device__ __forceinline__ void ldsm4(uint32_t (&r)[4], uint32_t a) {
    asm volatile("ldmatrix.sync.aligned.m8n8.x4.shared.b16 {%0,%1,%2,%3}, [%4];"
                 : "=r"(r[0]), "=r"(r[1]), "=r"(r[2]), "=r"(r[3]) : "r"(a) : "memory");
}
__device__ __forceinline__ void ldsm4t(uint32_t (&r)[4], uint32_t a) {
    asm volatile("ldmatrix.sync.aligned.m8n8.x4.trans.shared.b16 {%0,%1,%2,%3}, [%4];"
                 : "=r"(r[0]), "=r"(r[1]), "=r"(r[2]), "=r"(r[3]) : "r"(a) : "memory");
}
__device__ __forceinline__ void mma(float (&c)[4], const uint32_t (&a)[4], uint32_t b0, uint32_t b1) {
    asm("mma.sync.aligned.m16n8k16.row.col.f32.bf16.bf16.f32 {%0,%1,%2,%3}, {%4,%5,%6,%7}, {%8,%9}, {%0,%1,%2,%3};"
        : "+f"(c[0]), "+f"(c[1]), "+f"(c[2]), "+f"(c[3])
        : "r"(a[0]), "r"(a[1]), "r"(a[2]), "r"(a[3]), "r"(b0), "r"(b1));
}
__device__ __forceinline__ uint32_t mapa(uint32_t a, uint32_t cta) {
    uint32_t r;
    asm("mapa.shared::cluster.u32 %0, %1, %2;" : "=r"(r) : "r"(a), "r"(cta));
    return r;
}
__device__ __forceinline__ void st_async4(uint32_t rb, int off, int bar, float a, float b, float c, float d) {
    asm volatile("st.async.weak.shared::cluster.mbarrier::complete_tx::bytes.v4.f32 [%0], {%1,%2,%3,%4}, [%5];"
                 ::"r"(rb + off), "f"(a), "f"(b), "f"(c), "f"(d), "r"(rb + BARS + bar * 8) : "memory");
}
__device__ __forceinline__ void st_async2(uint32_t rb, int off, int bar, float a, float b) {
    asm volatile("st.async.weak.shared::cluster.mbarrier::complete_tx::bytes.v2.f32 [%0], {%1,%2}, [%3];"
                 ::"r"(rb + off), "f"(a), "f"(b), "r"(rb + BARS + bar * 8) : "memory");
}
__device__ __forceinline__ void bar_sync(int id, int n) { asm volatile("bar.sync %0, %1;" ::"r"(id), "r"(n) : "memory"); }
__device__ __forceinline__ void bar_arrive(int id, int n) { asm volatile("bar.arrive %0, %1;" ::"r"(id), "r"(n) : "memory"); }
__device__ __forceinline__ void cluster_wait() { asm volatile("barrier.cluster.wait.acquire.aligned;" ::: "memory"); }
__device__ __forceinline__ float4 lds128(uint32_t a) {
    float4 v;
    asm volatile("ld.shared.v4.f32 {%0,%1,%2,%3}, [%4];" : "=f"(v.x), "=f"(v.y), "=f"(v.z), "=f"(v.w) : "r"(a) : "memory");
    return v;
}
__device__ __forceinline__ float2 lds64(uint32_t a) {
    float2 v;
    asm volatile("ld.shared.v2.f32 {%0,%1}, [%2];" : "=f"(v.x), "=f"(v.y) : "r"(a) : "memory");
    return v;
}
__device__ __forceinline__ void sts16(uint32_t a, float v) {
    asm volatile("st.shared.u16 [%0], %1;" ::"r"(a), "h"(__bfloat16_as_ushort(__float2bfloat16_rn(v))) : "memory");
}
__device__ __forceinline__ float bf_lo(uint32_t w) { return __uint_as_float(w << 16); }
__device__ __forceinline__ float bf_hi(uint32_t w) { return __uint_as_float(w & 0xffff0000u); }
__device__ __forceinline__ uint32_t pack_bf(float lo, float hi) {
    __nv_bfloat162 v = __floats2bfloat162_rn(lo, hi);
    return *reinterpret_cast<uint32_t*>(&v);
}
__device__ __forceinline__ float wsum(float v) {
#pragma unroll
    for (int o = 16; o; o >>= 1) v += __shfl_xor_sync(0xffffffffu, v, o);
    return v;
}
__device__ __forceinline__ float wmax(float v) {
#pragma unroll
    for (int o = 16; o; o >>= 1) v = fmaxf(v, __shfl_xor_sync(0xffffffffu, v, o));
    return v;
}
__device__ __forceinline__ uint32_t sw64(uint32_t a) { return a ^ ((a >> 3) & 0x30u); }
__device__ __forceinline__ uint32_t sw128(uint32_t a) { return a ^ ((a >> 3) & 0x70u); }

__device__ __forceinline__ float lds_bf(uint32_t a) {
    uint16_t v;
    asm volatile("ld.shared.u16 %0, [%1];" : "=h"(v) : "r"(a) : "memory");
    return __uint_as_float((uint32_t)v << 16);
}
__device__ __forceinline__ float4 atom4(float* p, float a, float b, float c) {
    float4 o;
    asm volatile("atom.relaxed.gpu.global.add.v4.f32 {%0,%1,%2,%3}, [%4], {%5,%6,%7,%8};"
                 : "=f"(o.x), "=f"(o.y), "=f"(o.z), "=f"(o.w) : "l"(p), "f"(a), "f"(b), "f"(c), "f"(1.f) : "memory");
    return o;
}
__device__ __forceinline__ void finish(__nv_bfloat16* po, bool first, uint32_t epoch, float h0, float h1, float h2,
                                       float f0, float f1, float f2) {
    asm volatile("st.global.u16 [%0], %1;\nst.global.u16 [%0+32], %2;\nst.global.u16 [%0+64], %3;"
                 ::"l"(po), "h"(__bfloat16_as_ushort(__float2bfloat16_rn(h0 + bfr(f0)))),
                 "h"(__bfloat16_as_ushort(__float2bfloat16_rn(h1 + bfr(f1)))),
                 "h"(__bfloat16_as_ushort(__float2bfloat16_rn(h2 + bfr(f2)))) : "memory");
    if (first) g_epoch = epoch + 1;
}
__device__ __forceinline__ float4 sum6(uint32_t a, int stride) {
    float4 v[CL];
#pragma unroll
    for (int s = 0; s < CL; s++) v[s] = lds128(a + s * stride);
    return make_float4(((v[0].x + v[1].x) + (v[2].x + v[3].x)) + (v[4].x + v[5].x), ((v[0].y + v[1].y) + (v[2].y + v[3].y)) + (v[4].y + v[5].y),
                       ((v[0].z + v[1].z) + (v[2].z + v[3].z)) + (v[4].z + v[5].z), ((v[0].w + v[1].w) + (v[2].w + v[3].w)) + (v[4].w + v[5].w));
}
__device__ __forceinline__ float2 sum6h(uint32_t a, int stride) {
    float2 v[CL];
#pragma unroll
    for (int s = 0; s < CL; s++) v[s] = lds64(a + s * stride);
    return make_float2(((v[0].x + v[1].x) + (v[2].x + v[3].x)) + (v[4].x + v[5].x), ((v[0].y + v[1].y) + (v[2].y + v[3].y)) + (v[4].y + v[5].y));
}

template <int I>
__device__ __forceinline__ void produce(uint32_t sb, const CUtensorMap* mk, const CUtensorMap* mv, const CUtensorMap* mo,
                                        const CUtensorMap* m1, const CUtensorMap* m2, int c, int r, int key0, int nk,
                                        int lane, int& mine, int& landed, uint32_t t0) {
    if constexpr (I < NCHUNK) {
        constexpr int narrow = need_landed(I, narrow_window(I)), wide = need_landed(I, wide_window(I));
        const uint32_t bar = sb + BARS + I * 8;
        if constexpr (narrow > 0) {
            int it = 0;
            while (landed < narrow) {
                const uint32_t m = mbar_test_ballot(sb + BARS, mine, I);
                landed += __popc(m);
                mine += ((m >> lane) & 1u) << 5;
                if constexpr (wide < narrow) {
                    uint32_t now;
                    asm volatile("mov.u32 %0, %%globaltimer_lo;" : "=r"(now));
                    if (landed >= wide && (int)(now - t0) >= nominal_ns(I)) break;
                }
                if (++it > 8 * SPIN_LIMIT) __trap();
            }
        }
        if constexpr (I == B_V + WQ_OFF / 8192) mbar_wait(sb + BARS + B_QDONE * 8);
        if constexpr (I == B_WO) mbar_wait(sb + BARS + B_KDONE * 8);
        if constexpr (I == B_W2) mbar_wait(sb + BARS + B_PVDONE * 8);
        if constexpr (I < B_V) {
            if (I - B_K < nk) tma3_elect(sb + R2 + (I - B_K) * 8192, mk, 0, key0 + (I - B_K) * 192, bar);
        } else if constexpr (I < B_WO) {
            if (I - B_V < nk) tma3_elect(sb + R1 + (I - B_V) * 8192, mv, 0, key0 + (I - B_V) * 192, bar);
        } else if constexpr (I < B_W1) {
            tma3_elect(sb + WO_OFF + (I - B_WO) * 6144, mo, 3 * r, 256 * c + (I - B_WO) * 32, bar);
        } else if constexpr (I < B_W2) {
            tma3_elect(sb + W1_OFF + (I - B_W1) * 9216, m1, 9 * c, 96 * r + (I - B_W1) * 16, bar);
        } else {
            tma3_elect(sb + R1 + (I - B_W2) * 6144, m2, 3 * r, 288 * c + (I - B_W2) * 32, bar);
        }
        produce<I + 1>(sb, mk, mv, mo, m1, m2, c, r, key0, nk, lane, mine, landed, t0);
    }
}

__global__ void __cluster_dims__(CL, 1, 1) __launch_bounds__(NTHREADS, 1)
decode_layer_kernel(const __nv_bfloat16* __restrict__ x, const __nv_bfloat16* __restrict__ wq, __nv_bfloat16* __restrict__ out,
                    const __grid_constant__ CUtensorMap mq, const __grid_constant__ CUtensorMap mk, const __grid_constant__ CUtensorMap mv,
                    const __grid_constant__ CUtensorMap mo, const __grid_constant__ CUtensorMap m1,
                    const __grid_constant__ CUtensorMap m2) {
    extern __shared__ __align__(1024) unsigned char smem[];
    const int tid = threadIdx.x, lane = tid & 31;
    const int c = blockIdx.y, r = blockIdx.x;
    asm volatile("{\n.reg .pred p;\nsetp.lt.u32 p, %1, 384;\n@p prefetch.global.L2 [%0];\n}"
                 ::"l"(reinterpret_cast<const char*>(wq) + (uint32_t)(r * (96 * QD * 2) + c * 512 + (tid >> 2) * (QD * 2) + (tid & 3) * 128)), "r"(tid));
    const int warp = __shfl_sync(0xffffffffu, tid >> 5, 0);
    const uint32_t sb = (uint32_t)__cvta_generic_to_shared(smem);
    const int nk = r < 4 ? 11 : 10;
    const int g = lane >> 2, t = lane & 3;

    if (warp == 13) {
        uint32_t t0;
        asm volatile("mov.u32 %0, %%globaltimer_lo;" : "=r"(t0));
        const int key0 = c * SK + (SK - WIN) + 32 * r;
        if (lane == 0) {
            asm volatile("prefetch.tensormap [%0];" ::"l"(&mq) : "memory");
#pragma unroll
            for (int b = 0; b < B_K; b++) {
                mbar_init(sb + BARS + b * 8, 1);
                mbar_expect(sb + BARS + b * 8, chunk_bytes(b));
            }
            mbar_init(sb + BARS + B_AR * 8, 5);
            asm volatile("fence.mbarrier_init.release.cluster;" ::: "memory");
#pragma unroll
            for (int i = 0; i < B_K; i++) tma3(sb + WQ_OFF + i * 8192, &mq, 96 * r + i * 16, 4 * c, sb + BARS + i * 8);
            asm volatile("prefetch.tensormap [%0];" ::"l"(&mk) : "memory");
            asm volatile("prefetch.tensormap [%0];" ::"l"(&mv) : "memory");
            asm volatile("prefetch.tensormap [%0];" ::"l"(&mo) : "memory");
            asm volatile("prefetch.tensormap [%0];" ::"l"(&m1) : "memory");
            asm volatile("prefetch.tensormap [%0];" ::"l"(&m2) : "memory");
        }
        __syncthreads();
        asm volatile("barrier.cluster.arrive.relaxed.aligned;" ::: "memory");
        int mine = lane, landed = 0;
        produce<B_K>(sb, &mk, &mv, &mo, &m1, &m2, c, r, key0, nk, lane, mine, landed, t0);
        cluster_wait();
        return;
    }

    if (warp == 12) {
        const uint32_t* x32 = reinterpret_cast<const uint32_t*>(x);
        uint32_t xr[9];
#pragma unroll
        for (int i = 0; i < 9; i++) xr[i] = __ldg(x32 + lane + 32 * i);
        const uint32_t xs0 = __ldg(x32 + 48 * r + lane), xs1 = __ldg(x32 + 48 * r + 32 + (lane & 15));
        const int col = 48 * (lane >> 4) + (lane & 15);
        const float x0 = __bfloat162float(x[96 * r + col]), x1 = __bfloat162float(x[96 * r + col + 16]), x2 = __bfloat162float(x[96 * r + col + 32]);
        __syncthreads();
        asm volatile("barrier.cluster.arrive.relaxed.aligned;" ::: "memory");
        float s = 0.f;
#pragma unroll
        for (int i = 0; i < 9; i++) s += bf_lo(xr[i]) + bf_hi(xr[i]);
        const float mean = wsum(s) / DM;
        float v = 0.f;
#pragma unroll
        for (int i = 0; i < 9; i++) {
            const float a = bf_lo(xr[i]) - mean, b = bf_hi(xr[i]) - mean;
            v += a * a + b * b;
        }
        const float mb = bfr(mean), sd = bfr(sqrtf(bfr(bfr(wsum(v) / DM) + 1e-5f)));
        asm volatile("st.shared.u32 [%0], %1;" ::"r"(sb + XNV + lane * 4),
                     "r"(pack_bf(bfr(bf_lo(xs0) - mb) / sd, bfr(bf_hi(xs0) - mb) / sd)) : "memory");
        asm volatile("st.shared.u32 [%0], %1;" ::"r"(sb + XNV + 128 + (lane & 15) * 4),
                     "r"(pack_bf(bfr(bf_lo(xs1) - mb) / sd, bfr(bf_hi(xs1) - mb) / sd)) : "memory");
        bar_arrive(1, 288);
        uint32_t epoch;
        asm volatile("ld.global.u32 %0, [%1];" : "=r"(epoch) : "l"(&g_epoch) : "memory");
        const uint32_t par = epoch & 1u;
        if (c == 0) {
            *reinterpret_cast<float4*>(&g_acc[par ^ 1][0][r][lane * 4]) = make_float4(0.f, 0.f, 0.f, 0.f);
            *reinterpret_cast<float4*>(&g_acc[par ^ 1][1][r][lane * 4]) = make_float4(0.f, 0.f, 0.f, 0.f);
        }
        cluster_wait();
        mbar_wait(sb + BARS + B_B * 8);
        float a0, a1, a2, n;
        int it = 0;
        do {
            asm volatile("ld.relaxed.gpu.global.v4.f32 {%0,%1,%2,%3}, [%4];" : "=f"(a0), "=f"(a1), "=f"(a2), "=f"(n) : "l"(&g_acc[par][0][r][lane * 4]) : "memory");
            if (++it > SPIN_LIMIT) __trap();
        } while (n != N_ATT);
        const float h0 = bfr(x0 + bfr(a0)), h1 = bfr(x1 + bfr(a1)), h2 = bfr(x2 + bfr(a2));
        sts16(sb + HV + col * 2, h0); sts16(sb + HV + col * 2 + 32, h1); sts16(sb + HV + col * 2 + 64, h2);
        __syncwarp();
        if (lane == 0) mbar_arrive(sb + BARS + B_H * 8);
        const float ctr = __shfl_sync(0xffffffffu, h0, 0);
        const float d0 = h0 - ctr, d1 = h1 - ctr, d2 = h2 - ctr;
        float s1 = d0 + d1 + d2, s2 = d0 * d0 + d1 * d1 + d2 * d2;
#pragma unroll
        for (int o = 16; o; o >>= 1) {
            s1 += __shfl_xor_sync(0xffffffffu, s1, o);
            s2 += __shfl_xor_sync(0xffffffffu, s2, o);
        }
        if (lane < CL) st_async2(mapa(sb, lane), INST + r * 8, B_ST, ctr + s1 * (1.f / 96.f), s2 - s1 * s1 * (1.f / 96.f));
        if (c == 3) {
            const float4 o = atom4(&g_acc[par][1][r][lane * 4], h0, h1, h2);
            if (o.w == N_OUT - 1.f) finish(out + 96 * r + col, r == 0 && col == 0, epoch, h0, h1, h2, o.x, o.y, o.z);
        }
        return;
    }

    if (warp < 11) {
        const int b0 = B_K + 5 * warp;
        if (lane == 0) {
#pragma unroll
            for (int i = 0; i < 5; i++) {
                const int b = b0 + i;
                mbar_init(sb + BARS + b * 8, b == B_KDONE ? 11 : (b == B_QDONE || b == B_PVDONE) ? 8 : 1);
            }
        }
        __syncwarp();
        const int b = b0 + lane;
        if (lane < 5 && b < B_QDONE) {
            const uint32_t bytes = b < NCHUNK ? chunk_bytes(b) : b == B_ML ? 1056 : b == B_ST ? 48 : (b == B_A || b == B_B) ? 6144 : 6912;
            mbar_expect(sb + BARS + b * 8, (nk == 10 && (b == B_K + 10 || b == B_V + 10)) ? 0 : bytes);
        }
        asm volatile("fence.mbarrier_init.release.cluster;" ::: "memory");
    }
    __syncthreads();
    asm volatile("barrier.cluster.arrive.relaxed.aligned;" ::: "memory");
    uint32_t epoch = 0;
    if (warp < 6) asm volatile("ld.global.u32 %0, [%1];" : "=r"(epoch) : "l"(&g_epoch) : "memory");
    const uint32_t rb0 = mapa(sb, t), rb1 = mapa(sb, 4 + (t & 1));
    const int trow = (lane & 7) + 8 * (lane >> 4), tcol = (lane >> 3) & 1;

    if (warp < 8) {
        bar_sync(1, 288);
        uint32_t b[3][4];
#pragma unroll
        for (int u = 0; u < 3; u++) ldsm4(b[u], sb + XNV + u * 64 + (lane >> 3) * 16);
        float acc[2][4] = {};
#pragma unroll
        for (int s = 0; s < 6; s++) {
            mbar_wait(sb + BARS + (B_WQ + s) * 8);
#pragma unroll
            for (int n = 0; n < 2; n++) {
                uint32_t a[4];
                ldsm4t(a, sb + WQ_OFF + s * 8192 + (warp >> 1) * 2048 + sw128(trow * 128 + (4 * (warp & 1) + 2 * n + tcol) * 16));
                mma(acc[n], a, b[s >> 1][(s & 1) * 2], b[s >> 1][(s & 1) * 2 + 1]);
            }
        }
        cluster_wait();
        const int off = INA + r * 1024 + (warp * 8 + g) * 16;
        st_async4(rb0, off, B_A, acc[0][0], acc[0][2], acc[1][0], acc[1][2]);
        if (t < 2) st_async4(rb1, off, B_A, acc[0][0], acc[0][2], acc[1][0], acc[1][2]);
        if (lane == 0) mbar_arrive(sb + BARS + B_QDONE * 8);
    } else {
        cluster_wait();
        if (warp < 10) {
            const int i = tid - 256;
            mbar_wait_cl(sb + BARS + B_A * 8);
            const float4 v = sum6(sb + INA + i * 16, 1024);
            const int n = 32 * (i >> 3) + (i & 7);
            const uint32_t a = sb + QV + (n >> 7) * 272 + (n & 127) * 2;
            sts16(a, v.x); sts16(a + 16, v.y); sts16(a + 32, v.z); sts16(a + 48, v.w);
        }
    }

    if (warp < 11) {
        bar_sync(2, 352);
        float s0 = -INFINITY, s1 = -INFINITY, m0 = -INFINITY, m1v = -INFINITY, e0 = 0.f, e1 = 0.f, l0 = 0.f, l1 = 0.f;
        if (warp < nk) {
            uint32_t b[4][4];
#pragma unroll
            for (int u = 0; u < 4; u++) ldsm4(b[u], sb + QV + (lane & 1) * 272 + (4 * u + (lane >> 3)) * 16);
            float acc[2][4] = {};
            mbar_wait(sb + BARS + (B_K + warp) * 8);
            const uint32_t krow = ((lane & 7) + 8 * ((lane >> 3) & 1)) * 256 + (lane >> 4) * 16;
#pragma unroll
            for (int s = 0; s < 8; s++) {
#pragma unroll
                for (int n = 0; n < 2; n++) {
                    uint32_t a[4];
                    ldsm4(a, sb + R2 + warp * 8192 + sw128(krow + n * 4096 + s * 32));
                    mma(acc[n], a, b[s >> 1][(s & 1) * 2], b[s >> 1][(s & 1) * 2 + 1]);
                }
            }
            const float r0 = t == 0 ? acc[0][0] : t == 1 ? acc[0][2] : t == 2 ? acc[1][0] : acc[1][2];
            const float r1 = t == 0 ? acc[0][1] : t == 1 ? acc[0][3] : t == 2 ? acc[1][1] : acc[1][3];
            s0 = bfr(bfr(r0) * 0.08838834764831845f);
            s1 = bfr(bfr(r1) * 0.08838834764831845f);
            m0 = wmax(s0); m1v = wmax(s1);
            e0 = __expf(s0 - m0); e1 = __expf(s1 - m1v);
            l0 = wsum(e0); l1 = wsum(e1);
        }
        if (lane == 0) mbar_arrive(sb + BARS + B_KDONE * 8);
        if (lane < CL) st_async4(mapa(sb, lane), INML + (r * 11 + warp) * 16, B_ML, m0, m1v, l0, l1);
        mbar_wait_cl(sb + BARS + B_ML * 8);
        if (warp < nk) {
            const float4 u0 = lds128(sb + INML + lane * 16), u1 = lds128(sb + INML + (lane + 32) * 16);
            float4 u2 = make_float4(-INFINITY, -INFINITY, 0.f, 0.f);
            if (lane < 2) u2 = lds128(sb + INML + (lane + 64) * 16);
            const float M0 = wmax(fmaxf(fmaxf(u0.x, u1.x), u2.x)), M1 = wmax(fmaxf(fmaxf(u0.y, u1.y), u2.y));
            const float L0 = wsum(u0.z * __expf(u0.x - M0) + u1.z * __expf(u1.x - M0) + u2.z * __expf(u2.x - M0));
            const float L1 = wsum(u0.w * __expf(u0.y - M1) + u1.w * __expf(u1.y - M1) + u2.w * __expf(u2.y - M1));
            const uint32_t a = sb + PVV + (32 * warp + 8 * t + g) * 2;
            sts16(a, e0 * (__expf(m0 - M0) / L0));
            sts16(a + 704, e1 * (__expf(m1v - M1) / L1));
        }
    }

    if (warp < 8) {
        bar_sync(3, 352);
        float acc[2][4] = {};
        const uint32_t vrow = trow * 256 + (2 * warp + tcol) * 16;
#pragma unroll
        for (int j = 0; j < 11; j++) {
            if (j < nk) {
                uint32_t b[4], a0[4], a1[4];
                ldsm4(b, sb + PVV + (lane & 1) * 704 + j * 64 + (lane >> 3) * 16);
                mbar_wait(sb + BARS + (B_V + j) * 8);
                ldsm4t(a0, sb + R1 + j * 8192 + sw128(vrow));
                ldsm4t(a1, sb + R1 + j * 8192 + 4096 + sw128(vrow));
                mma(acc[0], a0, b[0], b[1]);
                mma(acc[1], a1, b[2], b[3]);
            }
        }
        const float v0 = acc[0][0] + acc[1][0], v1 = acc[0][1] + acc[1][1], v2 = acc[0][2] + acc[1][2], v3 = acc[0][3] + acc[1][3];
        const int off = INB + r * 1024 + (warp * 8 + g) * 16;
        st_async4(rb0, off, B_B, v0, v1, v2, v3);
        if (t < 2) st_async4(rb1, off, B_B, v0, v1, v2, v3);
        if (lane == 0) mbar_arrive(sb + BARS + B_PVDONE * 8);
    } else if (warp < 11) {
        bar_arrive(3, 352);
        if (warp < 10) {
            const int i = tid - 256;
            mbar_wait_cl(sb + BARS + B_B * 8);
            const float4 v = sum6(sb + INB + i * 16, 1024);
            const uint32_t a = sb + OV + (16 * (i >> 3) + (i & 7)) * 2;
            sts16(a, v.x); sts16(a + 256, v.y); sts16(a + 16, v.z); sts16(a + 272, v.w);
            bar_arrive(4, 256);
        }
    }

    if (warp < 6) {
        const int half = warp & 1, kg = warp >> 1;
        const uint32_t wrow = trow * 192 + (6 * half + tcol) * 16;
        const uint32_t wa[3] = {sw64(wrow), sw64(wrow + 32), sw64(wrow + 64)};
        float* accC = &g_acc[epoch & 1u][0][r][(half * 16 + (t & 1) * 8 + g) * 4];
        asm volatile("" ::"l"(accC) : "memory");
        {
            bar_sync(4, 256);
            float acc[3][2][4] = {};
#pragma unroll
            for (int i = 0; i < 3; i++) {
                const int j = kg + 3 * i;
                if (j < 8) {
                    uint32_t b[4];
                    ldsm4(b, sb + OV + j * 64 + (lane >> 3) * 16);
                    mbar_wait(sb + BARS + (B_WO + j) * 8);
#pragma unroll
                    for (int n = 0; n < 3; n++) {
                        uint32_t a0[4], a1[4];
                        ldsm4t(a0, sb + WO_OFF + j * 6144 + wa[n]);
                        ldsm4t(a1, sb + WO_OFF + j * 6144 + 3072 + wa[n]);
                        mma(acc[n][0], a0, b[0], b[1]);
                        mma(acc[n][1], a1, b[2], b[3]);
                    }
                }
            }
            float v[3];
#pragma unroll
            for (int n = 0; n < 3; n++) v[n] = t == 0 ? acc[n][0][0] + acc[n][1][0] : acc[n][0][2] + acc[n][1][2];
            const uint32_t slot = sb + INA + (half * 16 + (t & 1) * 8 + g) * 16;
            if (kg > 0) {
                if (t < 2) asm volatile("st.shared.v4.f32 [%0], {%1,%2,%3,%3};" ::"r"(slot + kg * 512), "f"(v[0]), "f"(v[1]), "f"(v[2]) : "memory");
                bar_arrive(5, 192);
            } else {
                bar_sync(5, 192);
                const float4 u1 = lds128(slot + 512), u2 = lds128(slot + 1024);
                if (t < 2)
                    asm volatile("red.relaxed.gpu.global.add.v4.f32 [%0], {%1,%2,%3,%4};"
                                 ::"l"(accC), "f"(v[0] + u1.x + u2.x), "f"(v[1] + u1.y + u2.y), "f"(v[2] + u1.z + u2.z), "f"(1.f) : "memory");
            }
        }
        uint32_t a[2][3][2][4], b[3][4];
#pragma unroll
        for (int i = 0; i < 2; i++) {
            const int j = kg + 3 * i;
            mbar_wait(sb + BARS + (B_W2 + j) * 8);
#pragma unroll
            for (int n = 0; n < 3; n++) {
                ldsm4t(a[i][n][0], sb + R1 + j * 6144 + wa[n]);
                ldsm4t(a[i][n][1], sb + R1 + j * 6144 + 3072 + wa[n]);
            }
        }
        const int col = 48 * half + 8 * (t & 1) + g;
        mbar_wait(sb + BARS + B_H * 8);
        const float h0 = lds_bf(sb + HV + col * 2), h1 = lds_bf(sb + HV + col * 2 + 32), h2 = lds_bf(sb + HV + col * 2 + 64);
        __nv_bfloat16* po = out + 96 * r + col;
        asm volatile("" : "+l"(po));
        mbar_wait(sb + BARS + B_AR * 8);
#pragma unroll
        for (int i = 0; i < 3; i++) ldsm4(b[i], sb + AV + (kg + 3 * i) * 64 + (lane >> 3) * 16);
        float acc[3][2][4] = {};
#pragma unroll
        for (int i = 0; i < 2; i++)
#pragma unroll
            for (int n = 0; n < 3; n++) {
                mma(acc[n][0], a[i][n][0], b[i][0], b[i][1]);
                mma(acc[n][1], a[i][n][1], b[i][2], b[i][3]);
            }
        mbar_spin(sb + BARS + (B_W2 + kg + 6) * 8);
#pragma unroll
        for (int n = 0; n < 3; n++) {
            ldsm4t(a[0][n][0], sb + R1 + (kg + 6) * 6144 + wa[n]);
            ldsm4t(a[0][n][1], sb + R1 + (kg + 6) * 6144 + 3072 + wa[n]);
        }
#pragma unroll
        for (int n = 0; n < 3; n++) {
            mma(acc[n][0], a[0][n][0], b[2][0], b[2][1]);
            mma(acc[n][1], a[0][n][1], b[2][2], b[2][3]);
        }
        if (t < 2) {
            float v[3];
#pragma unroll
            for (int n = 0; n < 3; n++) v[n] = t == 0 ? acc[n][0][0] + acc[n][1][0] : acc[n][0][2] + acc[n][1][2];
            const float4 o = atom4(accC + CL * 128, v[0], v[1], v[2]);
            if (o.w == N_OUT - 1.f) finish(po, r == 0 && col == 0, epoch, h0, h1, h2, o.x + (v[0] - h0), o.y + (v[1] - h1), o.z + (v[2] - h2));
        }
    } else {
        {
            const int w = warp - 6;
            uint32_t a[3][6][4];
            float cs[3][4] = {}, p[3][2][4] = {};
            const uint32_t arow = trow * 576 + (6 * w + tcol) * 16;
            auto send = [&](int box, int bar, float v0, float v1, float v2, float v3, float v4, float v5) {
                const int off4 = box + r * 1152 + (w * 8 + g) * 16, off2 = box + r * 1152 + 768 + (w * 8 + g) * 8;
                st_async4(rb0, off4, bar, v0, v1, v2, v3);
                st_async2(rb0, off2, bar, v4, v5);
                if (t < 2) {
                    st_async4(rb1, off4, bar, v0, v1, v2, v3);
                    st_async2(rb1, off2, bar, v4, v5);
                }
            };
#pragma unroll
            for (int s = 0; s < 6; s++) {
                mbar_wait(sb + BARS + (B_W1 + s) * 8);
#pragma unroll
                for (int n = 0; n < 3; n++) {
                    ldsm4t(a[n][s], sb + W1_OFF + s * 9216 + sw64(arow + n * 32));
                    mma(cs[n], a[n][s], 0x3f803f80u, 0x3f803f80u);
                }
            }
            send(INP2, B_P2, cs[0][0], cs[0][2], cs[1][0], cs[1][2], cs[2][0], cs[2][2]);
            mbar_wait(sb + BARS + B_H * 8);
#pragma unroll
            for (int u = 0; u < 3; u++) {
                uint32_t b[4];
                ldsm4(b, sb + HV + u * 64 + (lane >> 3) * 16);
#pragma unroll
                for (int n = 0; n < 3; n++) {
                    mma(p[n][0], a[n][2 * u], b[0], b[1]);
                    mma(p[n][1], a[n][2 * u + 1], b[2], b[3]);
                }
            }
            send(INP1, B_P1, p[0][0][0] + p[0][1][0], p[0][0][2] + p[0][1][2], p[1][0][0] + p[1][1][0], p[1][0][2] + p[1][1][2],
                 p[2][0][0] + p[2][1][0], p[2][0][2] + p[2][1][2]);
        }
        if (warp < 11) {
            const int i = min(tid - 192, 143);
            mbar_wait_cl(sb + BARS + B_P2 * 8);
            const float2 cs = sum6h(sb + INP2 + i * 8, 1152);
            mbar_wait_cl(sb + BARS + B_ST * 8);
            const float2 st = ln_stats(sb + INST);
            const float mb = st.x, rs = st.y;
            mbar_wait_cl(sb + BARS + B_P1 * 8);
            const float2 p = sum6h(sb + INP1 + i * 8, 1152);
            const float y0 = bfr((p.x - mb * cs.x) * rs), y1 = bfr((p.y - mb * cs.y) * rs);
            const uint32_t a = sb + AV + (i < 96 ? 48 * (i >> 4) + 16 * (i & 1) + ((i >> 1) & 7) : 48 * ((i - 96) >> 3) + 32 + (i & 7)) * 2;
            sts16(a, __fdividef(y0, 1.f + __expf(-y0)));
            sts16(a + 16, __fdividef(y1, 1.f + __expf(-y1)));
            __syncwarp();
            if (lane == 0) mbar_arrive(sb + BARS + B_AR * 8);
        }
    }
}

__device__ float f_q[QD], f_o[QD], f_h[DM], f_a[FF];

__device__ __forceinline__ float block_sum(float v, float* red) {
    v = wsum(v);
    __syncthreads();
    if ((threadIdx.x & 31) == 0) red[threadIdx.x >> 5] = v;
    __syncthreads();
    float s = 0.f;
    for (int i = 0; i < (int)(blockDim.x >> 5); i++) s += red[i];
    return s;
}
__device__ void fb_ln(const __nv_bfloat16* xb, const float* xf, float* xn, float* red) {
    float s = 0.f;
    for (int i = threadIdx.x; i < DM; i += blockDim.x) { xn[i] = xb ? __bfloat162float(xb[i]) : xf[i]; s += xn[i]; }
    const float mean = block_sum(s, red) / DM;
    float v = 0.f;
    for (int i = threadIdx.x; i < DM; i += blockDim.x) v += (xn[i] - mean) * (xn[i] - mean);
    const float sd = bfr(sqrtf(bfr(bfr(block_sum(v, red) / DM) + 1e-5f))), mb = bfr(mean);
    for (int i = threadIdx.x; i < DM; i += blockDim.x) xn[i] = bfr(bfr(xn[i] - mb) / sd);
    __syncthreads();
}
__global__ void fb_ln_gemv(const __nv_bfloat16* x, const __nv_bfloat16* w, int n, int mode) {
    __shared__ float xn[DM], red[8];
    fb_ln(mode == 0 ? x : nullptr, f_h, xn, red);
    const int j = blockIdx.x * blockDim.x + threadIdx.x;
    float s = 0.f;
    for (int k = 0; k < DM; k++) s += xn[k] * __bfloat162float(w[(size_t)k * n + j]);
    s = bfr(s);
    if (mode == 0) f_q[j] = s; else f_a[j] = bfr(s / (1.f + __expf(-s)));
}
__global__ void fb_attn(const __nv_bfloat16* kc, const __nv_bfloat16* vc) {
    __shared__ float p[WIN], red[8];
    const int h = blockIdx.x;
    const size_t base = ((size_t)(h >> 1) * SK + (SK - WIN)) * DH;
    float mx = -INFINITY;
    for (int k = threadIdx.x; k < WIN; k += blockDim.x) {
        float s = 0.f;
        for (int d = 0; d < DH; d++) s += f_q[h * DH + d] * __bfloat162float(kc[base + (size_t)k * DH + d]);
        p[k] = bfr(bfr(s) * 0.08838834764831845f);
        mx = fmaxf(mx, p[k]);
    }
    mx = wmax(mx);
    if ((threadIdx.x & 31) == 0) red[threadIdx.x >> 5] = mx;
    __syncthreads();
    for (int i = 0; i < (int)(blockDim.x >> 5); i++) mx = fmaxf(mx, red[i]);
    float l = 0.f;
    for (int k = threadIdx.x; k < WIN; k += blockDim.x) { p[k] = __expf(p[k] - mx); l += p[k]; }
    l = block_sum(l, red);
    float o = 0.f;
    for (int k = 0; k < WIN; k++) o += bfr(p[k] / l) * __bfloat162float(vc[base + (size_t)k * DH + threadIdx.x]);
    f_o[h * DH + threadIdx.x] = bfr(o);
}
__global__ void fb_out_gemv(const __nv_bfloat16* x, const __nv_bfloat16* w, int rows, int mode, __nv_bfloat16* out) {
    __shared__ float red[8][32];
    const int j = blockIdx.x * 32 + (threadIdx.x & 31);
    const float* v = mode == 0 ? f_o : f_a;
    float s = 0.f;
    for (int k = threadIdx.x >> 5; k < rows; k += 8) s += v[k] * __bfloat162float(w[(size_t)k * DM + j]);
    red[threadIdx.x >> 5][threadIdx.x & 31] = s;
    __syncthreads();
    if (threadIdx.x < 32) {
        s = 0.f;
        for (int i = 0; i < 8; i++) s += red[i][threadIdx.x];
        if (mode == 0) f_h[j] = bfr(__bfloat162float(x[j]) + bfr(s)); else out[j] = __float2bfloat16_rn(f_h[j] + bfr(s));
    }
}

typedef CUresult (*EncodeFn)(CUtensorMap*, CUtensorMapDataType, cuuint32_t, void*, const cuuint64_t*, const cuuint64_t*,
                             const cuuint32_t*, const cuuint32_t*, CUtensorMapInterleave, CUtensorMapSwizzle,
                             CUtensorMapL2promotion, CUtensorMapFloatOOBfill);

bool make_map(EncodeFn enc, CUtensorMap* m, const void* p, int rows, int cols, int inner, int groups, int boxrows,
              bool rows_first = false) {
    const int a = rows_first ? 2 : 1, b = 3 - a;
    cuuint64_t dim[3], str[3];
    cuuint32_t box[3];
    dim[0] = inner; dim[a] = cols / inner; dim[b] = rows;
    str[a - 1] = inner * 2; str[b - 1] = cols * 2;
    box[0] = inner; box[a] = groups; box[b] = boxrows;
    const cuuint32_t es[3] = {1, 1, 1};
    return enc(m, CU_TENSOR_MAP_DATA_TYPE_BFLOAT16, 3, const_cast<void*>(p), dim, str, box, es, CU_TENSOR_MAP_INTERLEAVE_NONE,
               inner == 64 ? CU_TENSOR_MAP_SWIZZLE_128B : CU_TENSOR_MAP_SWIZZLE_64B, CU_TENSOR_MAP_L2_PROMOTION_NONE,
               CU_TENSOR_MAP_FLOAT_OOB_FILL_NONE) == CUDA_SUCCESS;
}

}

extern "C" void kernel_launch(void* const* d_in, const int* in_sizes, int n_in, void* d_out, int out_size) {
    const __nv_bfloat16* x = (const __nv_bfloat16*)d_in[0];
    const __nv_bfloat16* kc = (const __nv_bfloat16*)d_in[1];
    const __nv_bfloat16* vc = (const __nv_bfloat16*)d_in[2];
    const __nv_bfloat16* wq = (const __nv_bfloat16*)d_in[3];
    const __nv_bfloat16* wo = (const __nv_bfloat16*)d_in[4];
    const __nv_bfloat16* w1 = (const __nv_bfloat16*)d_in[6];
    const __nv_bfloat16* w2 = (const __nv_bfloat16*)d_in[7];
    __nv_bfloat16* out = (__nv_bfloat16*)d_out;
    cudaStream_t stream = cudaStreamPerThread;

    static int state = 0;
    static EncodeFn enc = nullptr;
    if (state == 0) {
        state = 2;
        void* fn = nullptr;
        cudaDriverEntryPointQueryResult qr;
        if (cudaGetDriverEntryPoint("cuTensorMapEncodeTiled", &fn, cudaEnableDefault, &qr) == cudaSuccess &&
            qr == cudaDriverEntryPointSuccess && fn &&
            cudaFuncSetAttribute(decode_layer_kernel, cudaFuncAttributeMaxDynamicSharedMemorySize, SMEM_BYTES) == cudaSuccess) {
            enc = (EncodeFn)fn;
            cudaLaunchConfig_t cfg = {};
            cfg.gridDim = dim3(CL, HKV); cfg.blockDim = dim3(NTHREADS); cfg.dynamicSmemBytes = SMEM_BYTES;
            cudaLaunchAttribute at[1];
            at[0].id = cudaLaunchAttributeClusterDimension;
            at[0].val.clusterDim.x = CL; at[0].val.clusterDim.y = 1; at[0].val.clusterDim.z = 1;
            cfg.attrs = at; cfg.numAttrs = 1;
            int nc = 0;
            if (cudaOccupancyMaxActiveClusters(&nc, decode_layer_kernel, &cfg) == cudaSuccess && nc >= HKV) state = 1;
        }
        (void)cudaGetLastError();
    }
    CUtensorMap mq, mk, mv, mo, m1, m2;
    if (state == 1 && make_map(enc, &mq, wq, DM, QD, 64, 4, 16, true) && make_map(enc, &mk, kc, HKV * SK, DH, 64, 2, 32) &&
        make_map(enc, &mv, vc, HKV * SK, DH, 64, 2, 32) && make_map(enc, &mo, wo, QD, DM, 32, 3, 32) &&
        make_map(enc, &m1, w1, DM, FF, 32, 9, 16) && make_map(enc, &m2, w2, FF, DM, 32, 3, 32)) {
        decode_layer_kernel<<<dim3(CL, HKV), NTHREADS, SMEM_BYTES, stream>>>(x, wq, out, mq, mk, mv, mo, m1, m2);
        return;
    }
    fb_ln_gemv<<<QD / 128, 128, 0, stream>>>(x, wq, QD, 0);
    fb_attn<<<2 * HKV, 128, 0, stream>>>(kc, vc);
    fb_out_gemv<<<DM / 32, 256, 0, stream>>>(x, wo, QD, 0, out);
    fb_ln_gemv<<<FF / 128, 128, 0, stream>>>(x, w1, FF, 1);
    fb_out_gemv<<<DM / 32, 256, 0, stream>>>(x, w2, FF, 1, out);
}
```

```cpp
#include <cuda_runtime.h>
#include <cuda_bf16.h>
#include <cuda.h>
#include <stdint.h>

namespace {

constexpr int DM = 576, HKV = 16, SK = 8192, WIN = 2048, DH = 128, FF = 4608, QD = 4096;
constexpr int CL = 6;
constexpr int NWARPS = 14;
constexpr int NTHREADS = NWARPS * 32;

constexpr int R1 = 0;
constexpr int WQ_OFF = 90112 - 6 * 8192;
constexpr int R2 = 90112;
constexpr int WO_OFF = R2;
constexpr int W1_OFF = R2 + 49152;
constexpr int INA = R2 + 104448;
constexpr int INB = INA + 6144;
constexpr int INP2 = INB + 6144;
constexpr int INP1 = INP2 + 6912;
constexpr int INML = INP1 + 6912;
constexpr int INST = INML + 1088;
constexpr int XNV = INST + 64;
constexpr int QV = XNV + 192;
constexpr int PVV = QV + 544;
constexpr int OV = PVV + 1408;
constexpr int HV = OV + 512;
constexpr int AV = HV + 192;
constexpr int BARS = AV + 576;
constexpr int SMEM_BYTES = BARS + 64 * 8;
static_assert(SMEM_BYTES <= 232448, "smem");

constexpr int B_WQ = 0, B_K = 6, B_V = 17, B_WO = 28, B_W1 = 36, B_W2 = 42, NCHUNK = 51;
constexpr int B_A = 51, B_ML = 52, B_B = 53, B_P2 = 54, B_ST = 55, B_P1 = 56;
constexpr int B_QDONE = 57, B_KDONE = 58, B_PVDONE = 59, B_H = 60, B_AR = 61;
static_assert(B_K + 5 * 11 == B_AR && B_AR < 64, "barrier set-up below covers B_K .. B_H");

__host__ __device__ constexpr int chunk_bytes(int i) {
    return i < B_WO ? 8192 : i < B_W1 ? 6144 : i < B_W2 ? 9216 : 6144;
}
__host__ __device__ constexpr int by_phase(int i, int k, int v, int o, int a, int b) {
    return 1024 * (i < B_V ? k : i < B_WO ? v : i < B_W1 ? o : i < B_W2 ? a : b);
}
__host__ __device__ constexpr int narrow_window(int i) { return by_phase(i, 64, 40, 38, 38, 36); }
__host__ __device__ constexpr int wide_window(int i) { return by_phase(i, 64, 64, 64, 64, 48); }
constexpr int PACE_PS = 476;
constexpr int PACE_T0 = 550;
__host__ __device__ constexpr int need_landed(int i, int w) {
    int s = 0, j = i;
    while (j >= 0 && s + chunk_bytes(j) <= w) { s += chunk_bytes(j); j--; }
    return j + 1;
}
__host__ __device__ constexpr int nominal_ns(int i) {
    int cum = -44 * 1024 - (i >= B_V ? 2731 : 0) - (i >= B_WO ? 2731 : 0);
    for (int j = 0; j <= i; j++) cum += chunk_bytes(j);
    return PACE_T0 + cum / 16 * PACE_PS / 1000;
}

constexpr float N_ATT = 16.f;
constexpr float N_OUT = 49.f;
__device__ __align__(4096) float g_acc[2][2][8][128];
__device__ uint32_t g_epoch;

__device__ __forceinline__ float bfr(float v) {
    uint32_t w;
    asm("cvt.rn.bf16x2.f32 %0, %1, %2;" : "=r"(w) : "f"(v), "f"(0.f));
    return __uint_as_float(w);
}
__device__ __forceinline__ void mbar_init(uint32_t a, uint32_t c) {
    asm volatile("mbarrier.init.shared::cta.b64 [%0], %1;" ::"r"(a), "r"(c) : "memory");
}
__device__ __forceinline__ void mbar_expect(uint32_t a, uint32_t b) {
    asm volatile("mbarrier.arrive.expect_tx.shared::cta.b64 _, [%0], %1;" ::"r"(a), "r"(b) : "memory");
}
__device__ __forceinline__ void mbar_arrive(uint32_t a) {
    asm volatile("mbarrier.arrive.shared::cta.b64 _, [%0];" ::"r"(a) : "memory");
}
constexpr int SPIN_LIMIT = 1 << 21;
__device__ __forceinline__ void mbar_wait(uint32_t a) {
    uint32_t ok;
    int it = 0;
    do {
        asm volatile("{\n.reg .pred p;\nmbarrier.try_wait.parity.shared::cta.b64 p, [%1], 0;\nselp.u32 %0, 1, 0, p;\n}"
                     : "=r"(ok) : "r"(a) : "memory");
        if (++it > SPIN_LIMIT) __trap();
    } while (!ok);
}
__device__ __forceinline__ void mbar_spin(uint32_t a) {
    uint32_t ok;
    int it = 0;
    do {
        asm volatile("{\n.reg .pred p;\nmbarrier.test_wait.parity.shared::cta.b64 p, [%1], 0;\nselp.u32 %0, 1, 0, p;\n}"
                     : "=r"(ok) : "r"(a) : "memory");
        if (++it > 8 * SPIN_LIMIT) __trap();
    } while (!ok);
}
__device__ __forceinline__ float2 ln_stats(uint32_t a) {
    float4 u[3];
#pragma unroll
    for (int i = 0; i < 3; i++)
        asm volatile("ld.shared.v4.f32 {%0,%1,%2,%3}, [%4];" : "=f"(u[i].x), "=f"(u[i].y), "=f"(u[i].z), "=f"(u[i].w) : "r"(a + 16 * i) : "memory");
    const float mean = ((u[0].x + u[0].z) + (u[1].x + u[1].z) + (u[2].x + u[2].z)) * (1.f / 6.f);
    const float d0 = u[0].x - mean, d1 = u[0].z - mean, d2 = u[1].x - mean, d3 = u[1].z - mean, d4 = u[2].x - mean, d5 = u[2].z - mean;
    const float var = (((u[0].y + u[0].w) + (u[1].y + u[1].w) + (u[2].y + u[2].w)) +
                       96.f * ((d0 * d0 + d1 * d1) + (d2 * d2 + d3 * d3) + (d4 * d4 + d5 * d5))) * (1.f / 576.f);
    return make_float2(bfr(mean), 1.f / bfr(sqrtf(bfr(bfr(var) + 1e-5f))));
}
__device__ __forceinline__ uint32_t mbar_test_ballot(uint32_t bars, int idx, int lim) {
    uint32_t m;
    asm volatile("{\n.reg .pred p, q;\n.reg .u32 a;\nsetp.lt.s32 q, %2, %3;\nsetp.ne.u32 p, 0, 0;\nmad.lo.u32 a, %2, 8, %1;\n"
                 "@q mbarrier.test_wait.parity.shared::cta.b64 p, [a], 0;\nvote.sync.ballot.b32 %0, p, 0xffffffff;\n}"
                 : "=r"(m) : "r"(bars), "r"(idx), "r"(lim) : "memory");
    return m;
}
__device__ __forceinline__ void mbar_wait_cl(uint32_t a) {
    uint32_t ok;
    int it = 0;
    do {
        asm volatile("{\n.reg .pred p;\nmbarrier.try_wait.parity.acquire.cluster.shared::cta.b64 p, [%1], 0;\nselp.u32 %0, 1, 0, p;\n}"
                     : "=r"(ok) : "r"(a) : "memory");
        if (++it > SPIN_LIMIT) __trap();
    } while (!ok);
}
__device__ __forceinline__ void tma3(uint32_t dst, const CUtensorMap* m, int c1, int c2, uint32_t bar) {
    asm volatile("cp.async.bulk.tensor.3d.shared::cluster.global.mbarrier::complete_tx::bytes [%0], [%1, {%2, %3, %4}], [%5];"
                 ::"r"(dst), "l"(m), "r"(0), "r"(c1), "r"(c2), "r"(bar) : "memory");
}
__device__ __forceinline__ void tma3_elect(uint32_t dst, const CUtensorMap* m, int c1, int c2, uint32_t bar) {
    asm volatile("{\n.reg .pred p;\nelect.sync _|p, 0xffffffff;\n"
                 "@p cp.async.bulk.tensor.3d.shared::cluster.global.mbarrier::complete_tx::bytes [%0], [%1, {%2, %3, %4}], [%5];\n}"
                 ::"r"(dst), "l"(m), "r"(0), "r"(c1), "r"(c2), "r"(bar) : "memory");
}
__device__ __forceinline__ void ldsm4(uint32_t (&r)[4], uint32_t a) {
    asm volatile("ldmatrix.sync.aligned.m8n8.x4.shared.b16 {%0,%1,%2,%3}, [%4];"
                 : "=r"(r[0]), "=r"(r[1]), "=r"(r[2]), "=r"(r[3]) : "r"(a) : "memory");
}
__device__ __forceinline__ void ldsm4t(uint32_t (&r)[4], uint32_t a) {
    asm volatile("ldmatrix.sync.aligned.m8n8.x4.trans.shared.b16 {%0,%1,%2,%3}, [%4];"
                 : "=r"(r[0]), "=r"(r[1]), "=r"(r[2]), "=r"(r[3]) : "r"(a) : "memory");
}
__device__ __forceinline__ void mma(float (&c)[4], const uint32_t (&a)[4], uint32_t b0, uint32_t b1) {
    asm("mma.sync.aligned.m16n8k16.row.col.f32.bf16.bf16.f32 {%0,%1,%2,%3}, {%4,%5,%6,%7}, {%8,%9}, {%0,%1,%2,%3};"
        : "+f"(c[0]), "+f"(c[1]), "+f"(c[2]), "+f"(c[3])
        : "r"(a[0]), "r"(a[1]), "r"(a[2]), "r"(a[3]), "r"(b0), "r"(b1));
}
__device__ __forceinline__ uint32_t mapa(uint32_t a, uint32_t cta) {
    uint32_t r;
    asm("mapa.shared::cluster.u32 %0, %1, %2;" : "=r"(r) : "r"(a), "r"(cta));
    return r;
}
__device__ __forceinline__ void st_async4(uint32_t rb, int off, int bar, float a, float b, float c, float d) {
    asm volatile("st.async.weak.shared::cluster.mbarrier::complete_tx::bytes.v4.f32 [%0], {%1,%2,%3,%4}, [%5];"
                 ::"r"(rb + off), "f"(a), "f"(b), "f"(c), "f"(d), "r"(rb + BARS + bar * 8) : "memory");
}
__device__ __forceinline__ void st_async2(uint32_t rb, int off, int bar, float a, float b) {
    asm volatile("st.async.weak.shared::cluster.mbarrier::complete_tx::bytes.v2.f32 [%0], {%1,%2}, [%3];"
                 ::"r"(rb + off), "f"(a), "f"(b), "r"(rb + BARS + bar * 8) : "memory");
}
__device__ __forceinline__ void bar_sync(int id, int n) { asm volatile("bar.sync %0, %1;" ::"r"(id), "r"(n) : "memory"); }
__device__ __forceinline__ void bar_arrive(int id, int n) { asm volatile("bar.arrive %0, %1;" ::"r"(id), "r"(n) : "memory"); }
__device__ __forceinline__ void cluster_wait() { asm volatile("barrier.cluster.wait.acquire.aligned;" ::: "memory"); }
__device__ __forceinline__ float4 lds128(uint32_t a) {
    float4 v;
    asm volatile("ld.shared.v4.f32 {%0,%1,%2,%3}, [%4];" : "=f"(v.x), "=f"(v.y), "=f"(v.z), "=f"(v.w) : "r"(a) : "memory");
    return v;
}
__device__ __forceinline__ float2 lds64(uint32_t a) {
    float2 v;
    asm volatile("ld.shared.v2.f32 {%0,%1}, [%2];" : "=f"(v.x), "=f"(v.y) : "r"(a) : "memory");
    return v;
}
__device__ __forceinline__ void sts16(uint32_t a, float v) {
    asm volatile("st.shared.u16 [%0], %1;" ::"r"(a), "h"(__bfloat16_as_ushort(__float2bfloat16_rn(v))) : "memory");
}
__device__ __forceinline__ float bf_lo(uint32_t w) { return __uint_as_float(w << 16); }
__device__ __forceinline__ float bf_hi(uint32_t w) { return __uint_as_float(w & 0xffff0000u); }
__device__ __forceinline__ uint32_t pack_bf(float lo, float hi) {
    __nv_bfloat162 v = __floats2bfloat162_rn(lo, hi);
    return *reinterpret_cast<uint32_t*>(&v);
}
__device__ __forceinline__ float wsum(float v) {
#pragma unroll
    for (int o = 16; o; o >>= 1) v += __shfl_xor_sync(0xffffffffu, v, o);
    return v;
}
__device__ __forceinline__ float wmax(float v) {
#pragma unroll
    for (int o = 16; o; o >>= 1) v = fmaxf(v, __shfl_xor_sync(0xffffffffu, v, o));
    return v;
}
__device__ __forceinline__ uint32_t sw64(uint32_t a) { return a ^ ((a >> 3) & 0x30u); }
__device__ __forceinline__ uint32_t sw128(uint32_t a) { return a ^ ((a >> 3) & 0x70u); }

__device__ __forceinline__ float4 atom4(float* p, float a, float b, float c) {
    float4 o;
    asm volatile("atom.relaxed.gpu.global.add.v4.f32 {%0,%1,%2,%3}, [%4], {%5,%6,%7,%8};"
                 : "=f"(o.x), "=f"(o.y), "=f"(o.z), "=f"(o.w) : "l"(p), "f"(a), "f"(b), "f"(c), "f"(1.f) : "memory");
    return o;
}
__device__ __forceinline__ void finish(__nv_bfloat16* po, bool first, uint32_t epoch, float s0, float s1, float s2) {
    asm volatile("st.global.u16 [%0], %1;\nst.global.u16 [%0+32], %2;\nst.global.u16 [%0+64], %3;"
                 ::"l"(po), "h"(__bfloat16_as_ushort(__float2bfloat16_rn(s0))), "h"(__bfloat16_as_ushort(__float2bfloat16_rn(s1))),
                 "h"(__bfloat16_as_ushort(__float2bfloat16_rn(s2))) : "memory");
    if (first) g_epoch = epoch + 1;
}
__device__ __forceinline__ float4 sum6(uint32_t a, int stride) {
    float4 v[CL];
#pragma unroll
    for (int s = 0; s < CL; s++) v[s] = lds128(a + s * stride);
    return make_float4(((v[0].x + v[1].x) + (v[2].x + v[3].x)) + (v[4].x + v[5].x), ((v[0].y + v[1].y) + (v[2].y + v[3].y)) + (v[4].y + v[5].y),
                       ((v[0].z + v[1].z) + (v[2].z + v[3].z)) + (v[4].z + v[5].z), ((v[0].w + v[1].w) + (v[2].w + v[3].w)) + (v[4].w + v[5].w));
}
__device__ __forceinline__ float2 sum6h(uint32_t a, int stride) {
    float2 v[CL];
#pragma unroll
    for (int s = 0; s < CL; s++) v[s] = lds64(a + s * stride);
    return make_float2(((v[0].x + v[1].x) + (v[2].x + v[3].x)) + (v[4].x + v[5].x), ((v[0].y + v[1].y) + (v[2].y + v[3].y)) + (v[4].y + v[5].y));
}

template <int I>
__device__ __forceinline__ void produce(uint32_t sb, const CUtensorMap* mk, const CUtensorMap* mv, const CUtensorMap* mo,
                                        const CUtensorMap* m1, const CUtensorMap* m2, int c, int r, int key0, int nk,
                                        int lane, int& mine, int& landed, uint32_t t0) {
    if constexpr (I < NCHUNK) {
        constexpr int narrow = need_landed(I, narrow_window(I)), wide = need_landed(I, wide_window(I));
        const uint32_t bar = sb + BARS + I * 8;
        if constexpr (narrow > 0) {
            int it = 0;
            while (landed < narrow) {
                const uint32_t m = mbar_test_ballot(sb + BARS, mine, I);
                landed += __popc(m);
                mine += ((m >> lane) & 1u) << 5;
                if constexpr (wide < narrow) {
                    uint32_t now;
                    asm volatile("mov.u32 %0, %%globaltimer_lo;" : "=r"(now));
                    if (landed >= wide && (int)(now - t0) >= nominal_ns(I)) break;
                }
                if (++it > 8 * SPIN_LIMIT) __trap();
            }
        }
        if constexpr (I == B_V + WQ_OFF / 8192) mbar_wait(sb + BARS + B_QDONE * 8);
        if constexpr (I == B_WO) mbar_wait(sb + BARS + B_KDONE * 8);
        if constexpr (I == B_W2) mbar_wait(sb + BARS + B_PVDONE * 8);
        if constexpr (I < B_V) {
            if (I - B_K < nk) tma3_elect(sb + R2 + (I - B_K) * 8192, mk, 0, key0 + (I - B_K) * 192, bar);
        } else if constexpr (I < B_WO) {
            if (I - B_V < nk) tma3_elect(sb + R1 + (I - B_V) * 8192, mv, 0, key0 + (I - B_V) * 192, bar);
        } else if constexpr (I < B_W1) {
            tma3_elect(sb + WO_OFF + (I - B_WO) * 6144, mo, 3 * r, 256 * c + (I - B_WO) * 32, bar);
        } else if constexpr (I < B_W2) {
            tma3_elect(sb + W1_OFF + (I - B_W1) * 9216, m1, 9 * c, 96 * r + (I - B_W1) * 16, bar);
        } else {
            tma3_elect(sb + R1 + (I - B_W2) * 6144, m2, 3 * r, 288 * c + (I - B_W2) * 32, bar);
        }
        produce<I + 1>(sb, mk, mv, mo, m1, m2, c, r, key0, nk, lane, mine, landed, t0);
    }
}

__global__ void __cluster_dims__(CL, 1, 1) __launch_bounds__(NTHREADS, 1)
decode_layer_kernel(const __nv_bfloat16* __restrict__ x, const __nv_bfloat16* __restrict__ wq, __nv_bfloat16* __restrict__ out,
                    const __grid_constant__ CUtensorMap mq, const __grid_constant__ CUtensorMap mk, const __grid_constant__ CUtensorMap mv,
                    const __grid_constant__ CUtensorMap mo, const __grid_constant__ CUtensorMap m1,
                    const __grid_constant__ CUtensorMap m2) {
    extern __shared__ __align__(1024) unsigned char smem[];
    const int tid = threadIdx.x, lane = tid & 31;
    const int c = blockIdx.y, r = blockIdx.x;
    asm volatile("{\n.reg .pred p;\nsetp.lt.u32 p, %1, 384;\n@p prefetch.global.L2 [%0];\n}"
                 ::"l"(reinterpret_cast<const char*>(wq) + (uint32_t)(r * (96 * QD * 2) + c * 512 + (tid >> 2) * (QD * 2) + (tid & 3) * 128)), "r"(tid));
    const int warp = __shfl_sync(0xffffffffu, tid >> 5, 0);
    const uint32_t sb = (uint32_t)__cvta_generic_to_shared(smem);
    const int nk = r < 4 ? 11 : 10;
    const int g = lane >> 2, t = lane & 3;

    if (warp == 13) {
        uint32_t t0;
        asm volatile("mov.u32 %0, %%globaltimer_lo;" : "=r"(t0));
        const int key0 = c * SK + (SK - WIN) + 32 * r;
        if (lane == 0) {
            asm volatile("prefetch.tensormap [%0];" ::"l"(&mq) : "memory");
#pragma unroll
            for (int b = 0; b < B_K; b++) {
                mbar_init(sb + BARS + b * 8, 1);
                mbar_expect(sb + BARS + b * 8, chunk_bytes(b));
            }
            mbar_init(sb + BARS + B_AR * 8, 5);
            asm volatile("fence.mbarrier_init.release.cluster;" ::: "memory");
#pragma unroll
            for (int i = 0; i < B_K; i++) tma3(sb + WQ_OFF + i * 8192, &mq, 96 * r + i * 16, 4 * c, sb + BARS + i * 8);
            asm volatile("prefetch.tensormap [%0];" ::"l"(&mk) : "memory");
            asm volatile("prefetch.tensormap [%0];" ::"l"(&mv) : "memory");
            asm volatile("prefetch.tensormap [%0];" ::"l"(&mo) : "memory");
            asm volatile("prefetch.tensormap [%0];" ::"l"(&m1) : "memory");
            asm volatile("prefetch.tensormap [%0];" ::"l"(&m2) : "memory");
        }
        __syncthreads();
        asm volatile("barrier.cluster.arrive.relaxed.aligned;" ::: "memory");
        int mine = lane, landed = 0;
        produce<B_K>(sb, &mk, &mv, &mo, &m1, &m2, c, r, key0, nk, lane, mine, landed, t0);
        cluster_wait();
        return;
    }

    if (warp == 12) {
        const uint32_t* x32 = reinterpret_cast<const uint32_t*>(x);
        uint32_t xr[9];
#pragma unroll
        for (int i = 0; i < 9; i++) xr[i] = __ldg(x32 + lane + 32 * i);
        const uint32_t xs0 = __ldg(x32 + 48 * r + lane), xs1 = __ldg(x32 + 48 * r + 32 + (lane & 15));
        const int col = 48 * (lane >> 4) + (lane & 15);
        const float x0 = __bfloat162float(x[96 * r + col]), x1 = __bfloat162float(x[96 * r + col + 16]), x2 = __bfloat162float(x[96 * r + col + 32]);
        __syncthreads();
        asm volatile("barrier.cluster.arrive.relaxed.aligned;" ::: "memory");
        float s = 0.f;
#pragma unroll
        for (int i = 0; i < 9; i++) s += bf_lo(xr[i]) + bf_hi(xr[i]);
        const float mean = wsum(s) / DM;
        float v = 0.f;
#pragma unroll
        for (int i = 0; i < 9; i++) {
            const float a = bf_lo(xr[i]) - mean, b = bf_hi(xr[i]) - mean;
            v += a * a + b * b;
        }
        const float mb = bfr(mean), sd = bfr(sqrtf(bfr(bfr(wsum(v) / DM) + 1e-5f)));
        asm volatile("st.shared.u32 [%0], %1;" ::"r"(sb + XNV + lane * 4),
                     "r"(pack_bf(bfr(bf_lo(xs0) - mb) / sd, bfr(bf_hi(xs0) - mb) / sd)) : "memory");
        asm volatile("st.shared.u32 [%0], %1;" ::"r"(sb + XNV + 128 + (lane & 15) * 4),
                     "r"(pack_bf(bfr(bf_lo(xs1) - mb) / sd, bfr(bf_hi(xs1) - mb) / sd)) : "memory");
        bar_arrive(1, 288);
        uint32_t epoch;
        asm volatile("ld.global.u32 %0, [%1];" : "=r"(epoch) : "l"(&g_epoch) : "memory");
        const uint32_t par = epoch & 1u;
        if (c == 0) {
            *reinterpret_cast<float4*>(&g_acc[par ^ 1][0][r][lane * 4]) = make_float4(0.f, 0.f, 0.f, 0.f);
            *reinterpret_cast<float4*>(&g_acc[par ^ 1][1][r][lane * 4]) = make_float4(0.f, 0.f, 0.f, 0.f);
        }
        cluster_wait();
        mbar_wait(sb + BARS + B_B * 8);
        float a0, a1, a2, n;
        int it = 0;
        do {
            asm volatile("ld.relaxed.gpu.global.v4.f32 {%0,%1,%2,%3}, [%4];" : "=f"(a0), "=f"(a1), "=f"(a2), "=f"(n) : "l"(&g_acc[par][0][r][lane * 4]) : "memory");
            if (++it > SPIN_LIMIT) __trap();
        } while (n != N_ATT);
        const float h0 = bfr(x0 + bfr(a0)), h1 = bfr(x1 + bfr(a1)), h2 = bfr(x2 + bfr(a2));
        sts16(sb + HV + col * 2, h0); sts16(sb + HV + col * 2 + 32, h1); sts16(sb + HV + col * 2 + 64, h2);
        __syncwarp();
        if (lane == 0) mbar_arrive(sb + BARS + B_H * 8);
        const float ctr = __shfl_sync(0xffffffffu, h0, 0);
        const float d0 = h0 - ctr, d1 = h1 - ctr, d2 = h2 - ctr;
        float s1 = d0 + d1 + d2, s2 = d0 * d0 + d1 * d1 + d2 * d2;
#pragma unroll
        for (int o = 16; o; o >>= 1) {
            s1 += __shfl_xor_sync(0xffffffffu, s1, o);
            s2 += __shfl_xor_sync(0xffffffffu, s2, o);
        }
        if (lane < CL) st_async2(mapa(sb, lane), INST + r * 8, B_ST, ctr + s1 * (1.f / 96.f), s2 - s1 * s1 * (1.f / 96.f));
        if (c == 3) {
            const float4 o = atom4(&g_acc[par][1][r][lane * 4], h0, h1, h2);
            if (o.w == N_OUT - 1.f) finish(out + 96 * r + col, r == 0 && col == 0, epoch, o.x + h0, o.y + h1, o.z + h2);
        }
        return;
    }

    if (warp < 11) {
        const int b0 = B_K + 5 * warp;
        if (lane == 0) {
#pragma unroll
            for (int i = 0; i < 5; i++) {
                const int b = b0 + i;
                mbar_init(sb + BARS + b * 8, b == B_KDONE ? 11 : (b == B_QDONE || b == B_PVDONE) ? 8 : 1);
            }
        }
        __syncwarp();
        const int b = b0 + lane;
        if (lane < 5 && b < B_QDONE) {
            const uint32_t bytes = b < NCHUNK ? chunk_bytes(b) : b == B_ML ? 1056 : b == B_ST ? 48 : (b == B_A || b == B_B) ? 6144 : 6912;
            mbar_expect(sb + BARS + b * 8, (nk == 10 && (b == B_K + 10 || b == B_V + 10)) ? 0 : bytes);
        }
        asm volatile("fence.mbarrier_init.release.cluster;" ::: "memory");
    }
    __syncthreads();
    asm volatile("barrier.cluster.arrive.relaxed.aligned;" ::: "memory");
    uint32_t epoch = 0;
    if (warp < 6) asm volatile("ld.global.u32 %0, [%1];" : "=r"(epoch) : "l"(&g_epoch) : "memory");
    const uint32_t rb0 = mapa(sb, t), rb1 = mapa(sb, 4 + (t & 1));
    const int trow = (lane & 7) + 8 * (lane >> 4), tcol = (lane >> 3) & 1;

    if (warp < 8) {
        bar_sync(1, 288);
        uint32_t b[3][4];
#pragma unroll
        for (int u = 0; u < 3; u++) ldsm4(b[u], sb + XNV + u * 64 + (lane >> 3) * 16);
        float acc[2][4] = {};
#pragma unroll
        for (int s = 0; s < 6; s++) {
            mbar_wait(sb + BARS + (B_WQ + s) * 8);
#pragma unroll
            for (int n = 0; n < 2; n++) {
                uint32_t a[4];
                ldsm4t(a, sb + WQ_OFF + s * 8192 + (warp >> 1) * 2048 + sw128(trow * 128 + (4 * (warp & 1) + 2 * n + tcol) * 16));
                mma(acc[n], a, b[s >> 1][(s & 1) * 2], b[s >> 1][(s & 1) * 2 + 1]);
            }
        }
        cluster_wait();
        const int off = INA + r * 1024 + (warp * 8 + g) * 16;
        st_async4(rb0, off, B_A, acc[0][0], acc[0][2], acc[1][0], acc[1][2]);
        if (t < 2) st_async4(rb1, off, B_A, acc[0][0], acc[0][2], acc[1][0], acc[1][2]);
        if (lane == 0) mbar_arrive(sb + BARS + B_QDONE * 8);
    } else {
        cluster_wait();
        if (warp < 10) {
            const int i = tid - 256;
            mbar_wait_cl(sb + BARS + B_A * 8);
            const float4 v = sum6(sb + INA + i * 16, 1024);
            const int n = 32 * (i >> 3) + (i & 7);
            const uint32_t a = sb + QV + (n >> 7) * 272 + (n & 127) * 2;
            sts16(a, v.x); sts16(a + 16, v.y); sts16(a + 32, v.z); sts16(a + 48, v.w);
        }
    }

    if (warp < 11) {
        bar_sync(2, 352);
        float s0 = -INFINITY, s1 = -INFINITY, m0 = -INFINITY, m1v = -INFINITY, e0 = 0.f, e1 = 0.f, l0 = 0.f, l1 = 0.f;
        if (warp < nk) {
            uint32_t b[4][4];
#pragma unroll
            for (int u = 0; u < 4; u++) ldsm4(b[u], sb + QV + (lane & 1) * 272 + (4 * u + (lane >> 3)) * 16);
            float acc[2][4] = {};
            mbar_wait(sb + BARS + (B_K + warp) * 8);
            const uint32_t krow = ((lane & 7) + 8 * ((lane >> 3) & 1)) * 256 + (lane >> 4) * 16;
#pragma unroll
            for (int s = 0; s < 8; s++) {
#pragma unroll
                for (int n = 0; n < 2; n++) {
                    uint32_t a[4];
                    ldsm4(a, sb + R2 + warp * 8192 + sw128(krow + n * 4096 + s * 32));
                    mma(acc[n], a, b[s >> 1][(s & 1) * 2], b[s >> 1][(s & 1) * 2 + 1]);
                }
            }
            const float r0 = t == 0 ? acc[0][0] : t == 1 ? acc[0][2] : t == 2 ? acc[1][0] : acc[1][2];
            const float r1 = t == 0 ? acc[0][1] : t == 1 ? acc[0][3] : t == 2 ? acc[1][1] : acc[1][3];
            s0 = bfr(bfr(r0) * 0.08838834764831845f);
            s1 = bfr(bfr(r1) * 0.08838834764831845f);
            m0 = wmax(s0); m1v = wmax(s1);
            e0 = __expf(s0 - m0); e1 = __expf(s1 - m1v);
            l0 = wsum(e0); l1 = wsum(e1);
        }
        if (lane == 0) mbar_arrive(sb + BARS + B_KDONE * 8);
        if (lane < CL) st_async4(mapa(sb, lane), INML + (r * 11 + warp) * 16, B_ML, m0, m1v, l0, l1);
        mbar_wait_cl(sb + BARS + B_ML * 8);
        if (warp < nk) {
            const float4 u0 = lds128(sb + INML + lane * 16), u1 = lds128(sb + INML + (lane + 32) * 16);
            float4 u2 = make_float4(-INFINITY, -INFINITY, 0.f, 0.f);
            if (lane < 2) u2 = lds128(sb + INML + (lane + 64) * 16);
            const float M0 = wmax(fmaxf(fmaxf(u0.x, u1.x), u2.x)), M1 = wmax(fmaxf(fmaxf(u0.y, u1.y), u2.y));
            const float L0 = wsum(u0.z * __expf(u0.x - M0) + u1.z * __expf(u1.x - M0) + u2.z * __expf(u2.x - M0));
            const float L1 = wsum(u0.w * __expf(u0.y - M1) + u1.w * __expf(u1.y - M1) + u2.w * __expf(u2.y - M1));
            const uint32_t a = sb + PVV + (32 * warp + 8 * t + g) * 2;
            sts16(a, e0 * (__expf(m0 - M0) / L0));
            sts16(a + 704, e1 * (__expf(m1v - M1) / L1));
        }
    }

    if (warp < 8) {
        bar_sync(3, 352);
        float acc[2][4] = {};
        const uint32_t vrow = trow * 256 + (2 * warp + tcol) * 16;
#pragma unroll
        for (int j = 0; j < 11; j++) {
            if (j < nk) {
                uint32_t b[4], a0[4], a1[4];
                ldsm4(b, sb + PVV + (lane & 1) * 704 + j * 64 + (lane >> 3) * 16);
                mbar_wait(sb + BARS + (B_V + j) * 8);
                ldsm4t(a0, sb + R1 + j * 8192 + sw128(vrow));
                ldsm4t(a1, sb + R1 + j * 8192 + 4096 + sw128(vrow));
                mma(acc[0], a0, b[0], b[1]);
                mma(acc[1], a1, b[2], b[3]);
            }
        }
        const float v0 = acc[0][0] + acc[1][0], v1 = acc[0][1] + acc[1][1], v2 = acc[0][2] + acc[1][2], v3 = acc[0][3] + acc[1][3];
        const int off = INB + r * 1024 + (warp * 8 + g) * 16;
        st_async4(rb0, off, B_B, v0, v1, v2, v3);
        if (t < 2) st_async4(rb1, off, B_B, v0, v1, v2, v3);
        if (lane == 0) mbar_arrive(sb + BARS + B_PVDONE * 8);
    } else if (warp < 11) {
        bar_arrive(3, 352);
        if (warp < 10) {
            const int i = tid - 256;
            mbar_wait_cl(sb + BARS + B_B * 8);
            const float4 v = sum6(sb + INB + i * 16, 1024);
            const uint32_t a = sb + OV + (16 * (i >> 3) + (i & 7)) * 2;
            sts16(a, v.x); sts16(a + 256, v.y); sts16(a + 16, v.z); sts16(a + 272, v.w);
            bar_arrive(4, 256);
        }
    }

    if (warp < 6) {
        const int half = warp & 1, kg = warp >> 1;
        const uint32_t wrow = trow * 192 + (6 * half + tcol) * 16;
        const uint32_t wa[3] = {sw64(wrow), sw64(wrow + 32), sw64(wrow + 64)};
        float* accC = &g_acc[epoch & 1u][0][r][(half * 16 + (t & 1) * 8 + g) * 4];
        asm volatile("" ::"l"(accC) : "memory");
        {
            bar_sync(4, 256);
            float acc[3][2][4] = {};
#pragma unroll
            for (int i = 0; i < 3; i++) {
                const int j = kg + 3 * i;
                if (j < 8) {
                    uint32_t b[4];
                    ldsm4(b, sb + OV + j * 64 + (lane >> 3) * 16);
                    mbar_wait(sb + BARS + (B_WO + j) * 8);
#pragma unroll
                    for (int n = 0; n < 3; n++) {
                        uint32_t a0[4], a1[4];
                        ldsm4t(a0, sb + WO_OFF + j * 6144 + wa[n]);
                        ldsm4t(a1, sb + WO_OFF + j * 6144 + 3072 + wa[n]);
                        mma(acc[n][0], a0, b[0], b[1]);
                        mma(acc[n][1], a1, b[2], b[3]);
                    }
                }
            }
            float v[3];
#pragma unroll
            for (int n = 0; n < 3; n++) v[n] = t == 0 ? acc[n][0][0] + acc[n][1][0] : acc[n][0][2] + acc[n][1][2];
            const uint32_t slot = sb + INA + (half * 16 + (t & 1) * 8 + g) * 16;
            if (kg > 0) {
                if (t < 2) asm volatile("st.shared.v4.f32 [%0], {%1,%2,%3,%3};" ::"r"(slot + kg * 512), "f"(v[0]), "f"(v[1]), "f"(v[2]) : "memory");
                bar_arrive(5, 192);
            } else {
                bar_sync(5, 192);
                const float4 u1 = lds128(slot + 512), u2 = lds128(slot + 1024);
                if (t < 2)
                    asm volatile("red.relaxed.gpu.global.add.v4.f32 [%0], {%1,%2,%3,%4};"
                                 ::"l"(accC), "f"(v[0] + u1.x + u2.x), "f"(v[1] + u1.y + u2.y), "f"(v[2] + u1.z + u2.z), "f"(1.f) : "memory");
            }
        }
        uint32_t a[2][3][2][4], b[3][4];
#pragma unroll
        for (int i = 0; i < 2; i++) {
            const int j = kg + 3 * i;
            mbar_wait(sb + BARS + (B_W2 + j) * 8);
#pragma unroll
            for (int n = 0; n < 3; n++) {
                ldsm4t(a[i][n][0], sb + R1 + j * 6144 + wa[n]);
                ldsm4t(a[i][n][1], sb + R1 + j * 6144 + 3072 + wa[n]);
            }
        }
        const int col = 48 * half + 8 * (t & 1) + g;
        __nv_bfloat16* po = out + 96 * r + col;
        asm volatile("" : "+l"(po));
        mbar_wait(sb + BARS + B_AR * 8);
#pragma unroll
        for (int i = 0; i < 3; i++) ldsm4(b[i], sb + AV + (kg + 3 * i) * 64 + (lane >> 3) * 16);
        float acc[3][2][4] = {};
#pragma unroll
        for (int i = 0; i < 2; i++)
#pragma unroll
            for (int n = 0; n < 3; n++) {
                mma(acc[n][0], a[i][n][0], b[i][0], b[i][1]);
                mma(acc[n][1], a[i][n][1], b[i][2], b[i][3]);
            }
        mbar_spin(sb + BARS + (B_W2 + kg + 6) * 8);
#pragma unroll
        for (int n = 0; n < 3; n++) {
            ldsm4t(a[0][n][0], sb + R1 + (kg + 6) * 6144 + wa[n]);
            ldsm4t(a[0][n][1], sb + R1 + (kg + 6) * 6144 + 3072 + wa[n]);
        }
#pragma unroll
        for (int n = 0; n < 3; n++) {
            mma(acc[n][0], a[0][n][0], b[2][0], b[2][1]);
            mma(acc[n][1], a[0][n][1], b[2][2], b[2][3]);
        }
        if (t < 2) {
            float v[3];
#pragma unroll
            for (int n = 0; n < 3; n++) v[n] = t == 0 ? acc[n][0][0] + acc[n][1][0] : acc[n][0][2] + acc[n][1][2];
            const float4 o = atom4(accC + 8 * 128, v[0], v[1], v[2]);
            if (o.w == N_OUT - 1.f) finish(po, r == 0 && col == 0, epoch, o.x + v[0], o.y + v[1], o.z + v[2]);
        }
    } else {
        {
            const int w = warp - 6;
            uint32_t a[3][6][4];
            float cs[3][4] = {}, p[3][2][4] = {};
            const uint32_t arow = trow * 576 + (6 * w + tcol) * 16;
            auto send = [&](int box, int bar, float v0, float v1, float v2, float v3, float v4, float v5) {
                const int off4 = box + r * 1152 + (w * 8 + g) * 16, off2 = box + r * 1152 + 768 + (w * 8 + g) * 8;
                st_async4(rb0, off4, bar, v0, v1, v2, v3);
                st_async2(rb0, off2, bar, v4, v5);
                if (t < 2) {
                    st_async4(rb1, off4, bar, v0, v1, v2, v3);
                    st_async2(rb1, off2, bar, v4, v5);
                }
            };
#pragma unroll
            for (int s = 0; s < 6; s++) {
                mbar_wait(sb + BARS + (B_W1 + s) * 8);
#pragma unroll
                for (int n = 0; n < 3; n++) {
                    ldsm4t(a[n][s], sb + W1_OFF + s * 9216 + sw64(arow + n * 32));
                    mma(cs[n], a[n][s], 0x3f803f80u, 0x3f803f80u);
                }
            }
            send(INP2, B_P2, cs[0][0], cs[0][2], cs[1][0], cs[1][2], cs[2][0], cs[2][2]);
            mbar_wait(sb + BARS + B_H * 8);
#pragma unroll
            for (int u = 0; u < 3; u++) {
                uint32_t b[4];
                ldsm4(b, sb + HV + u * 64 + (lane >> 3) * 16);
#pragma unroll
                for (int n = 0; n < 3; n++) {
                    mma(p[n][0], a[n][2 * u], b[0], b[1]);
                    mma(p[n][1], a[n][2 * u + 1], b[2], b[3]);
                }
            }
            send(INP1, B_P1, p[0][0][0] + p[0][1][0], p[0][0][2] + p[0][1][2], p[1][0][0] + p[1][1][0], p[1][0][2] + p[1][1][2],
                 p[2][0][0] + p[2][1][0], p[2][0][2] + p[2][1][2]);
        }
        if (warp < 11) {
            const int i = min(tid - 192, 143);
            mbar_wait_cl(sb + BARS + B_P2 * 8);
            const float2 cs = sum6h(sb + INP2 + i * 8, 1152);
            mbar_wait_cl(sb + BARS + B_ST * 8);
            const float2 st = ln_stats(sb + INST);
            const float mb = st.x, rs = st.y;
            mbar_wait_cl(sb + BARS + B_P1 * 8);
            const float2 p = sum6h(sb + INP1 + i * 8, 1152);
            const float y0 = bfr((p.x - mb * cs.x) * rs), y1 = bfr((p.y - mb * cs.y) * rs);
            const uint32_t a = sb + AV + (i < 96 ? 48 * (i >> 4) + 16 * (i & 1) + ((i >> 1) & 7) : 48 * ((i - 96) >> 3) + 32 + (i & 7)) * 2;
            sts16(a, __fdividef(y0, 1.f + __expf(-y0)));
            sts16(a + 16, __fdividef(y1, 1.f + __expf(-y1)));
            __syncwarp();
            if (lane == 0) mbar_arrive(sb + BARS + B_AR * 8);
        }
    }
}

__device__ float f_q[QD], f_o[QD], f_h[DM], f_a[FF];

__device__ __forceinline__ float block_sum(float v, float* red) {
    v = wsum(v);
    __syncthreads();
    if ((threadIdx.x & 31) == 0) red[threadIdx.x >> 5] = v;
    __syncthreads();
    float s = 0.f;
    for (int i = 0; i < (int)(blockDim.x >> 5); i++) s += red[i];
    return s;
}
__device__ void fb_ln(const __nv_bfloat16* xb, const float* xf, float* xn, float* red) {
    float s = 0.f;
    for (int i = threadIdx.x; i < DM; i += blockDim.x) { xn[i] = xb ? __bfloat162float(xb[i]) : xf[i]; s += xn[i]; }
    const float mean = block_sum(s, red) / DM;
    float v = 0.f;
    for (int i = threadIdx.x; i < DM; i += blockDim.x) v += (xn[i] - mean) * (xn[i] - mean);
    const float sd = bfr(sqrtf(bfr(bfr(block_sum(v, red) / DM) + 1e-5f))), mb = bfr(mean);
    for (int i = threadIdx.x; i < DM; i += blockDim.x) xn[i] = bfr(bfr(xn[i] - mb) / sd);
    __syncthreads();
}
__global__ void fb_ln_gemv(const __nv_bfloat16* x, const __nv_bfloat16* w, int n, int mode) {
    __shared__ float xn[DM], red[8];
    fb_ln(mode == 0 ? x : nullptr, f_h, xn, red);
    const int j = blockIdx.x * blockDim.x + threadIdx.x;
    float s = 0.f;
    for (int k = 0; k < DM; k++) s += xn[k] * __bfloat162float(w[(size_t)k * n + j]);
    s = bfr(s);
    if (mode == 0) f_q[j] = s; else f_a[j] = bfr(s / (1.f + __expf(-s)));
}
__global__ void fb_attn(const __nv_bfloat16* kc, const __nv_bfloat16* vc) {
    __shared__ float p[WIN], red[8];
    const int h = blockIdx.x;
    const size_t base = ((size_t)(h >> 1) * SK + (SK - WIN)) * DH;
    float mx = -INFINITY;
    for (int k = threadIdx.x; k < WIN; k += blockDim.x) {
        float s = 0.f;
        for (int d = 0; d < DH; d++) s += f_q[h * DH + d] * __bfloat162float(kc[base + (size_t)k * DH + d]);
        p[k] = bfr(bfr(s) * 0.08838834764831845f);
        mx = fmaxf(mx, p[k]);
    }
    mx = wmax(mx);
    if ((threadIdx.x & 31) == 0) red[threadIdx.x >> 5] = mx;
    __syncthreads();
    for (int i = 0; i < (int)(blockDim.x >> 5); i++) mx = fmaxf(mx, red[i]);
    float l = 0.f;
    for (int k = threadIdx.x; k < WIN; k += blockDim.x) { p[k] = __expf(p[k] - mx); l += p[k]; }
    l = block_sum(l, red);
    float o = 0.f;
    for (int k = 0; k < WIN; k++) o += bfr(p[k] / l) * __bfloat162float(vc[base + (size_t)k * DH + threadIdx.x]);
    f_o[h * DH + threadIdx.x] = bfr(o);
}
__global__ void fb_out_gemv(const __nv_bfloat16* x, const __nv_bfloat16* w, int rows, int mode, __nv_bfloat16* out) {
    __shared__ float red[8][32];
    const int j = blockIdx.x * 32 + (threadIdx.x & 31);
    const float* v = mode == 0 ? f_o : f_a;
    float s = 0.f;
    for (int k = threadIdx.x >> 5; k < rows; k += 8) s += v[k] * __bfloat162float(w[(size_t)k * DM + j]);
    red[threadIdx.x >> 5][threadIdx.x & 31] = s;
    __syncthreads();
    if (threadIdx.x < 32) {
        s = 0.f;
        for (int i = 0; i < 8; i++) s += red[i][threadIdx.x];
        if (mode == 0) f_h[j] = bfr(__bfloat162float(x[j]) + bfr(s)); else out[j] = __float2bfloat16_rn(f_h[j] + bfr(s));
    }
}

typedef CUresult (*EncodeFn)(CUtensorMap*, CUtensorMapDataType, cuuint32_t, void*, const cuuint64_t*, const cuuint64_t*,
                             const cuuint32_t*, const cuuint32_t*, CUtensorMapInterleave, CUtensorMapSwizzle,
                             CUtensorMapL2promotion, CUtensorMapFloatOOBfill);

bool make_map(EncodeFn enc, CUtensorMap* m, const void* p, int rows, int cols, int inner, int groups, int boxrows,
              bool rows_first = false) {
    const int a = rows_first ? 2 : 1, b = 3 - a;
    cuuint64_t dim[3], str[3];
    cuuint32_t box[3];
    dim[0] = inner; dim[a] = cols / inner; dim[b] = rows;
    str[a - 1] = inner * 2; str[b - 1] = cols * 2;
    box[0] = inner; box[a] = groups; box[b] = boxrows;
    const cuuint32_t es[3] = {1, 1, 1};
    return enc(m, CU_TENSOR_MAP_DATA_TYPE_BFLOAT16, 3, const_cast<void*>(p), dim, str, box, es, CU_TENSOR_MAP_INTERLEAVE_NONE,
               inner == 64 ? CU_TENSOR_MAP_SWIZZLE_128B : CU_TENSOR_MAP_SWIZZLE_64B, CU_TENSOR_MAP_L2_PROMOTION_NONE,
               CU_TENSOR_MAP_FLOAT_OOB_FILL_NONE) == CUDA_SUCCESS;
}

}

extern "C" void kernel_launch(void* const* d_in, const int* in_sizes, int n_in, void* d_out, int out_size) {
    const __nv_bfloat16* x = (const __nv_bfloat16*)d_in[0];
    const __nv_bfloat16* kc = (const __nv_bfloat16*)d_in[1];
    const __nv_bfloat16* vc = (const __nv_bfloat16*)d_in[2];
    const __nv_bfloat16* wq = (const __nv_bfloat16*)d_in[3];
    const __nv_bfloat16* wo = (const __nv_bfloat16*)d_in[4];
    const __nv_bfloat16* w1 = (const __nv_bfloat16*)d_in[6];
    const __nv_bfloat16* w2 = (const __nv_bfloat16*)d_in[7];
    __nv_bfloat16* out = (__nv_bfloat16*)d_out;
    cudaStream_t stream = cudaStreamPerThread;

    static int state = 0;
    static EncodeFn enc = nullptr;
    if (state == 0) {
        state = 2;
        void* fn = nullptr;
        cudaDriverEntryPointQueryResult qr;
        if (cudaGetDriverEntryPoint("cuTensorMapEncodeTiled", &fn, cudaEnableDefault, &qr) == cudaSuccess &&
            qr == cudaDriverEntryPointSuccess && fn &&
            cudaFuncSetAttribute(decode_layer_kernel, cudaFuncAttributeMaxDynamicSharedMemorySize, SMEM_BYTES) == cudaSuccess) {
            enc = (EncodeFn)fn;
            cudaLaunchConfig_t cfg = {};
            cfg.gridDim = dim3(CL, HKV); cfg.blockDim = dim3(NTHREADS); cfg.dynamicSmemBytes = SMEM_BYTES;
            cudaLaunchAttribute at[1];
            at[0].id = cudaLaunchAttributeClusterDimension;
            at[0].val.clusterDim.x = CL; at[0].val.clusterDim.y = 1; at[0].val.clusterDim.z = 1;
            cfg.attrs = at; cfg.numAttrs = 1;
            int nc = 0;
            if (cudaOccupancyMaxActiveClusters(&nc, decode_layer_kernel, &cfg) == cudaSuccess && nc >= HKV) state = 1;
        }
        (void)cudaGetLastError();
    }
    CUtensorMap mq, mk, mv, mo, m1, m2;
    if (state == 1 && make_map(enc, &mq, wq, DM, QD, 64, 4, 16, true) && make_map(enc, &mk, kc, HKV * SK, DH, 64, 2, 32) &&
        make_map(enc, &mv, vc, HKV * SK, DH, 64, 2, 32) && make_map(enc, &mo, wo, QD, DM, 32, 3, 32) &&
        make_map(enc, &m1, w1, DM, FF, 32, 9, 16) && make_map(enc, &m2, w2, FF, DM, 32, 3, 32)) {
        decode_layer_kernel<<<dim3(CL, HKV), NTHREADS, SMEM_BYTES, stream>>>(x, wq, out, mq, mk, mv, mo, m1, m2);
        return;
    }
    fb_ln_gemv<<<QD / 128, 128, 0, stream>>>(x, wq, QD, 0);
    fb_attn<<<2 * HKV, 128, 0, stream>>>(kc, vc);
    fb_out_gemv<<<DM / 32, 256, 0, stream>>>(x, wo, QD, 0, out);
    fb_ln_gemv<<<FF / 128, 128, 0, stream>>>(x, w1, FF, 1);
    fb_out_gemv<<<DM / 32, 256, 0, stream>>>(x, w2, FF, 1, out);
}
```
